```python
import torch

def _softmax(x, axis=-1):
    return torch.softmax(x, dim=axis)
def _gelu(x):
    return torch.nn.functional.gelu(x, approximate="tanh")
def _silu(x):
    return torch.nn.functional.silu(x)
def _sigmoid(x):
    return torch.sigmoid(x)
def _layernorm(x, axis=-1, eps=1e-5):
    m = x.mean(dim=axis, keepdim=True)
    v = x.var(dim=axis, keepdim=True, unbiased=False)
    return (x - m) / torch.sqrt(v + eps)
def _scatter_add(tgt, idx, src, axis=0):
    return tgt.clone().index_add_(axis, idx, src)
def _segment_sum(src, seg, n):
    out = torch.zeros((n,) + src.shape[1:], dtype=src.dtype)
    return out.index_add_(0, seg, src)
def _pad(x, pw):
    flat = tuple(v for pair in reversed(pw) for v in pair)
    return torch.nn.functional.pad(x, flat)

kernel_name = 'recurrent_scan__sliding_local_dilated__mixer_token_mlp__prompt'

def setup_inputs():

    _w = (lambda a: (lambda t: t.to(torch.bfloat16) if t.is_floating_point() else t)(torch.as_tensor(a)))
    def _A_setup():
        B, S, D = 1, 2048, 512
        return {
            "x": _w((lambda *s: torch.randn(*s, dtype=torch.bfloat16) * 0.05)(B, S, D)),
            "wqkv": _w((lambda *s: torch.randn(*s, dtype=torch.bfloat16) * 0.2)(D, 3 * D)),
            "wo": _w((lambda *s: torch.randn(*s, dtype=torch.bfloat16) * 0.2)(D, D)),
        }
    _A_in = _A_setup()

    def _B_setup():
        B, S, D, F = 1, 2048, 512, 1792
        return {
            "x": _w((lambda *s: torch.randn(*s, dtype=torch.bfloat16) * 0.05)(B, S, D)),
            "w1": _w((lambda *s: torch.randn(*s, dtype=torch.bfloat16) * 0.8)(S, F) * (S ** -0.5)),
            "b1": _w((lambda *s: torch.randn(*s, dtype=torch.bfloat16) * 12.8)(F) * 0.02),
            "w2": _w((lambda *s: torch.randn(*s, dtype=torch.bfloat16) * 0.8)(F, S) * (F ** -0.5)),
            "b2": _w((lambda *s: torch.randn(*s, dtype=torch.bfloat16) * 12.8)(S) * 0.02),
        }
    _B_in = _B_setup()

    return {
        "A_x": _A_in["x"],
        "A_wqkv": _A_in["wqkv"],
        "A_wo": _A_in["wo"],
        "B_x": _B_in["x"],
        "B_w1": _B_in["w1"],
        "B_b1": _B_in["b1"],
        "B_w2": _B_in["w2"],
        "B_b2": _B_in["b2"],
    }

def reference(A_x, A_wqkv, A_wo, B_x, B_w1, B_b1, B_w2, B_b2):
    def _A_ref(x, wqkv, wo):
        B, S, D = x.shape
        H = 32; Dh = D // H
        W, dil = 8, 2
        qkv = (lambda x, *d: x.permute(*d))((x @ wqkv).reshape(B, S, 3, H, Dh), 2, 0, 3, 1, 4)
        q, k, v = qkv[0], qkv[1], qkv[2]
        scale = Dh ** -0.5
        pos = torch.arange(S)
        off = torch.arange(W) * dil
        idx = pos[:, None] - off[None, :]
        mask = idx >= 0
        idx_c = torch.where(mask, idx, 0).reshape(-1)
        kg = k[:, :, idx_c, :].reshape(B, H, S, W, Dh)
        vg = v[:, :, idx_c, :].reshape(B, H, S, W, Dh)
        logits = torch.einsum("bhsd,bhswd->bhsw", q, kg) * scale
        logits = torch.where(mask[None, None, :, :], logits, -1e9)
        attn = _softmax(logits, axis=-1)
        o = torch.einsum("bhsw,bhswd->bhsd", attn, vg)
        return (lambda x, *d: x.permute(*d))(o, 0, 2, 1, 3).reshape(B, S, D) @ wo

    def _B_ref(x, w1, b1, w2, b2):
        B, S, D = x.shape
        h = _layernorm(x, axis=-1)
        u = torch.einsum("bsd,sf->bdf", h, w1) + b1
        u = _gelu(u)
        y = torch.einsum("bdf,fs->bds", u, w2) + b2
        return (lambda x, *d: x.permute(*d))(y, 0, 2, 1)

    x = A_x
    xn = _layernorm(x, axis=-1)
    s = _A_ref(xn, A_wqkv, A_wo)
    g = _silu(_B_ref(xn, B_w1, B_b1, B_w2, B_b2))
    return x + s * g
```

```cpp
#include <cuda_runtime.h>
#include <cuda_bf16.h>
#include <cuda.h>
#include <stdint.h>
#include <stdio.h>

namespace {

typedef __nv_bfloat16 bf16;
constexpr int S_ = 2048, D_ = 512, F_ = 1792;
constexpr int NSTG = 6, SLOT = 32768;
constexpr int XB_OFF = NSTG * SLOT;
constexpr int BAR_OFF = XB_OFF + 32768;
constexpr int SMEM_BYTES = BAR_OFF + 512 + 1024;
constexpr int B_FULL = 0, B_EMPTY = 48, B_XFULL = 96, B_XFREE = 160, B_EPOCH = 168, W_EPOCH = 176;
constexpr int SPIN_LIMIT = 1 << 22;

struct Maps { CUtensorMap x2, wq, w1, h, o, wo, w2, u, xr; };
struct Ptrs { const bf16 *x, *b1, *b2, *w1, *w2, *wo; bf16* out; };

__device__ __align__(1024) bf16 g_h[S_ * D_];
__device__ __align__(1024) bf16 g_u[F_ * D_];
__device__ __align__(1024) bf16 g_o[S_ * D_];
__device__ __align__(128) unsigned long long g_stats[S_];
__device__ __align__(128) uint4 g_halo[16 * 8 * 2 * 4 * 32];
__device__ __align__(128) uint4 g_park[128 * 2 * 6 * 32];
__device__ __align__(128) unsigned g_hflag[16 * 8 * 2];
__device__ __align__(128) unsigned g_cnt[32 * 32];
__device__ unsigned g_epoch;
#define PROF_T(i) do {} while (0)

__device__ __forceinline__ uint32_t smem_u32(const void* p) { return (uint32_t)__cvta_generic_to_shared(p); }
__device__ __forceinline__ void mbar_init(uint32_t b, uint32_t c) { asm volatile("mbarrier.init.shared::cta.b64 [%0], %1;" ::"r"(b), "r"(c) : "memory"); }
__device__ __forceinline__ void mbar_expect_tx(uint32_t b, uint32_t n) { asm volatile("mbarrier.arrive.expect_tx.shared::cta.b64 _, [%0], %1;" ::"r"(b), "r"(n) : "memory"); }
__device__ __forceinline__ void mbar_arrive(uint32_t b) { asm volatile("mbarrier.arrive.shared::cta.b64 _, [%0];" ::"r"(b) : "memory"); }
__device__ __forceinline__ void mbar_arrive_remote(uint32_t rb) { asm volatile("mbarrier.arrive.shared::cluster.b64 _, [%0];" ::"r"(rb) : "memory"); }
__device__ __forceinline__ bool mbar_try(uint32_t b, uint32_t par) {
  uint32_t ok;
  asm volatile("{\n.reg .pred p;\nmbarrier.try_wait.parity.shared::cta.b64 p, [%1], %2;\nselp.u32 %0, 1, 0, p;\n}" : "=r"(ok) : "r"(b), "r"(par) : "memory");
  return ok;
}
__device__ __forceinline__ void mbar_wait(uint32_t b, uint32_t par) {
  if (mbar_try(b, par)) return;
  int it = 0;
  while (!mbar_try(b, par)) { if (++it > SPIN_LIMIT) __trap(); }
}
__device__ __forceinline__ uint32_t mapa(uint32_t a, uint32_t cta) { uint32_t r; asm("mapa.shared::cluster.u32 %0, %1, %2;" : "=r"(r) : "r"(a), "r"(cta)); return r; }
__device__ __forceinline__ void tma2d(uint32_t dst, const CUtensorMap* m, int c0, int c1, uint32_t bar) {
  asm volatile("cp.async.bulk.tensor.2d.shared::cluster.global.mbarrier::complete_tx::bytes [%0], [%1, {%3, %4}], [%2];"
               ::"r"(dst), "l"(m), "r"(bar), "r"(c0), "r"(c1) : "memory");
}
__device__ __forceinline__ void prefetch_map(const CUtensorMap* m) { asm volatile("prefetch.tensormap [%0];" ::"l"(m) : "memory"); }
__device__ __forceinline__ void prefetch_l2(const void* p, uint32_t bytes) { asm volatile("cp.async.bulk.prefetch.L2.global [%0], %1;" ::"l"(p), "r"(bytes) : "memory"); }
__device__ __forceinline__ bool elect_one() { uint32_t p; asm volatile("{\n.reg .pred P;\nelect.sync _|P, 0xffffffff;\nselp.u32 %0, 1, 0, P;\n}" : "=r"(p)); return p; }
__device__ __forceinline__ void bar_arrive(int id, int n) { asm volatile("bar.arrive %0, %1;" ::"r"(id), "r"(n) : "memory"); }
__device__ __forceinline__ void bar_sync(int id, int n) { asm volatile("bar.sync %0, %1;" ::"r"(id), "r"(n) : "memory"); }
__device__ __forceinline__ void wg_fence() { asm volatile("wgmma.fence.sync.aligned;" ::: "memory"); }
__device__ __forceinline__ void wg_commit() { asm volatile("wgmma.commit_group.sync.aligned;" ::: "memory"); }
template <int N> __device__ __forceinline__ void wg_wait() { asm volatile("wgmma.wait_group.sync.aligned %0;" ::"n"(N) : "memory"); }
__device__ __forceinline__ uint64_t make_desc(uint32_t addr, uint32_t lbo, uint32_t sbo) {
  return (uint64_t)(((addr & 0x3FFFF) >> 4) | ((lbo >> 4) << 16)) | ((uint64_t)((sbo >> 4) | (1u << 30)) << 32);
}
__device__ __forceinline__ void fence_gpu() { asm volatile("fence.acq_rel.gpu;" ::: "memory"); }
__device__ __forceinline__ void fence_proxy_async() { asm volatile("fence.proxy.async;" ::: "memory"); }
__device__ __forceinline__ void red_add(unsigned* p, unsigned v) { asm volatile("red.relaxed.gpu.global.add.u32 [%0], %1;" ::"l"(p), "r"(v) : "memory"); }
__device__ __forceinline__ unsigned ld_acquire(const unsigned* p) { unsigned v; asm volatile("ld.acquire.gpu.global.u32 %0, [%1];" : "=r"(v) : "l"(p) : "memory"); return v; }
__device__ __forceinline__ unsigned ld_relaxed(const unsigned* p) { unsigned v; asm volatile("ld.relaxed.gpu.global.u32 %0, [%1];" : "=r"(v) : "l"(p) : "memory"); return v; }
__device__ __forceinline__ void st_relaxed(unsigned* p, unsigned v) { asm volatile("st.relaxed.gpu.global.u32 [%0], %1;" ::"l"(p), "r"(v) : "memory"); }
__device__ __forceinline__ unsigned long long ld_relaxed64(const unsigned long long* p) { unsigned long long v; asm volatile("ld.relaxed.gpu.global.u64 %0, [%1];" : "=l"(v) : "l"(p) : "memory"); return v; }
__device__ __forceinline__ void st_relaxed64(unsigned long long* p, unsigned long long v) { asm volatile("st.relaxed.gpu.global.u64 [%0], %1;" ::"l"(p), "l"(v) : "memory"); }
__device__ __forceinline__ void wait_cnt(const unsigned* p, unsigned target) {
  int it = 0;
  while ((int)(ld_acquire(p) - target) < 0) { if (++it > SPIN_LIMIT) __trap(); }
}
__device__ __forceinline__ uint4 ldg_cg(const void* p) { uint4 v; asm volatile("ld.global.cg.v4.u32 {%0,%1,%2,%3}, [%4];" : "=r"(v.x), "=r"(v.y), "=r"(v.z), "=r"(v.w) : "l"(p) : "memory"); return v; }
__device__ __forceinline__ void stg(void* p, uint4 v) { asm volatile("st.global.v4.u32 [%0], {%1,%2,%3,%4};" ::"l"(p), "r"(v.x), "r"(v.y), "r"(v.z), "r"(v.w) : "memory"); }
__device__ __forceinline__ uint4 lds128(uint32_t a) { uint4 v; asm volatile("ld.shared.v4.u32 {%0,%1,%2,%3}, [%4];" : "=r"(v.x), "=r"(v.y), "=r"(v.z), "=r"(v.w) : "r"(a) : "memory"); return v; }
__device__ __forceinline__ void sts128(uint32_t a, uint32_t x, uint32_t y, uint32_t z, uint32_t w) { asm volatile("st.shared.v4.u32 [%0], {%1,%2,%3,%4};" ::"r"(a), "r"(x), "r"(y), "r"(z), "r"(w) : "memory"); }
__device__ __forceinline__ void ldsm4(uint32_t a, uint32_t (&r)[4]) { asm volatile("ldmatrix.sync.aligned.m8n8.x4.shared.b16 {%0,%1,%2,%3}, [%4];" : "=r"(r[0]), "=r"(r[1]), "=r"(r[2]), "=r"(r[3]) : "r"(a) : "memory"); }
__device__ __forceinline__ void stsm4(uint32_t a, uint32_t r0, uint32_t r1, uint32_t r2, uint32_t r3) { asm volatile("stmatrix.sync.aligned.m8n8.x4.shared.b16 [%0], {%1,%2,%3,%4};" ::"r"(a), "r"(r0), "r"(r1), "r"(r2), "r"(r3) : "memory"); }
__device__ __forceinline__ void st_async4(uint32_t ra, float a, float b, float c, float d, uint32_t rbar) {
  asm volatile("st.async.weak.shared::cluster.mbarrier::complete_tx::bytes.v4.f32 [%0], {%1,%2,%3,%4}, [%5];" ::"r"(ra), "f"(a), "f"(b), "f"(c), "f"(d), "r"(rbar) : "memory");
}
__device__ __forceinline__ uint32_t movm(uint32_t a) { uint32_t d; asm volatile("movmatrix.sync.aligned.m8n8.trans.b16 %0, %1;" : "=r"(d) : "r"(a)); return d; }
__device__ __forceinline__ void mma16(float (&c)[4], uint32_t a0, uint32_t a1, uint32_t a2, uint32_t a3, uint32_t b0, uint32_t b1) {
  asm volatile("mma.sync.aligned.m16n8k16.row.col.f32.bf16.bf16.f32 {%0,%1,%2,%3}, {%4,%5,%6,%7}, {%8,%9}, {%0,%1,%2,%3};"
               : "+f"(c[0]), "+f"(c[1]), "+f"(c[2]), "+f"(c[3]) : "r"(a0), "r"(a1), "r"(a2), "r"(a3), "r"(b0), "r"(b1));
}
__device__ __forceinline__ void mma8(float (&c)[4], uint32_t a0, uint32_t a1, uint32_t b0) {
  asm volatile("mma.sync.aligned.m16n8k8.row.col.f32.bf16.bf16.f32 {%0,%1,%2,%3}, {%4,%5}, {%6}, {%0,%1,%2,%3};"
               : "+f"(c[0]), "+f"(c[1]), "+f"(c[2]), "+f"(c[3]) : "r"(a0), "r"(a1), "r"(b0));
}
__device__ __forceinline__ uint32_t pack2(float lo, float hi) { uint32_t d; asm("cvt.rn.bf16x2.f32 %0, %1, %2;" : "=r"(d) : "f"(hi), "f"(lo)); return d; }
__device__ __forceinline__ float lo_f(uint32_t v) { return __uint_as_float(v << 16); }
__device__ __forceinline__ float hi_f(uint32_t v) { return __uint_as_float(v & 0xffff0000u); }
__device__ __forceinline__ float rbf(float v) { return __bfloat162float(__float2bfloat16_rn(v)); }
__device__ __forceinline__ uint32_t hadd2(uint32_t a, uint32_t b) { uint32_t d; asm("add.rn.bf16x2 %0, %1, %2;" : "=r"(d) : "r"(a), "r"(b)); return d; }
__device__ __forceinline__ uint32_t hsub2(uint32_t a, uint32_t b) { uint32_t d; asm("sub.rn.bf16x2 %0, %1, %2;" : "=r"(d) : "r"(a), "r"(b)); return d; }
__device__ __forceinline__ uint32_t hmul2(uint32_t a, uint32_t b) { uint32_t d; asm("mul.rn.bf16x2 %0, %1, %2;" : "=r"(d) : "r"(a), "r"(b)); return d; }
__device__ __forceinline__ uint32_t hmax2(uint32_t a, uint32_t b) { uint32_t d; asm("max.bf16x2 %0, %1, %2;" : "=r"(d) : "r"(a), "r"(b)); return d; }
__device__ __forceinline__ float ex2(float x) { float y; asm("ex2.approx.ftz.f32 %0, %1;" : "=f"(y) : "f"(x)); return y; }
__device__ __forceinline__ float rcp(float x) { float y; asm("rcp.approx.ftz.f32 %0, %1;" : "=f"(y) : "f"(x)); return y; }
__device__ __forceinline__ float tanh_(float x) { float y; asm("tanh.approx.f32 %0, %1;" : "=f"(y) : "f"(x)); return y; }
__device__ __forceinline__ uint32_t norm2(uint32_t x, uint32_t m2, float rs) {
  uint32_t t = hsub2(x, m2);
  return pack2(lo_f(t) * rs, hi_f(t) * rs);
}

template <int TB>
__device__ __forceinline__ void wgmma_rs_n192(float (&d)[96], const uint32_t (&a)[4], uint64_t db, int scale_d) {
  asm volatile(
      "{\n.reg .pred p;\nsetp.ne.b32 p, %101, 0;\n"
      "wgmma.mma_async.sync.aligned.m64n192k16.f32.bf16.bf16 "
      "{%0, %1, %2, %3, %4, %5, %6, %7, %8, %9, %10, %11, %12, %13, %14, %15, %16, %17, %18, %19, %20, %21, %22, %23, %24, %25, %26, %27, %28, %29, %30, %31, %32, %33, %34, %35, %36, %37, %38, %39, %40, %41, %42, %43, %44, %45, %46, %47, %48, %49, %50, %51, %52, %53, %54, %55, %56, %57, %58, %59, %60, %61, %62, %63, %64, %65, %66, %67, %68, %69, %70, %71, %72, %73, %74, %75, %76, %77, %78, %79, %80, %81, %82, %83, %84, %85, %86, %87, %88, %89, %90, %91, %92, %93, %94, %95}, "
      "{%96, %97, %98, %99}, %100, p, 1, 1, %102;\n}\n"
      :
      "+f"(d[0]), "+f"(d[1]), "+f"(d[2]), "+f"(d[3]), "+f"(d[4]), "+f"(d[5]), "+f"(d[6]), "+f"(d[7]),
      "+f"(d[8]), "+f"(d[9]), "+f"(d[10]), "+f"(d[11]), "+f"(d[12]), "+f"(d[13]), "+f"(d[14]), "+f"(d[15]),
      "+f"(d[16]), "+f"(d[17]), "+f"(d[18]), "+f"(d[19]), "+f"(d[20]), "+f"(d[21]), "+f"(d[22]), "+f"(d[23]),
      "+f"(d[24]), "+f"(d[25]), "+f"(d[26]), "+f"(d[27]), "+f"(d[28]), "+f"(d[29]), "+f"(d[30]), "+f"(d[31]),
      "+f"(d[32]), "+f"(d[33]), "+f"(d[34]), "+f"(d[35]), "+f"(d[36]), "+f"(d[37]), "+f"(d[38]), "+f"(d[39]),
      "+f"(d[40]), "+f"(d[41]), "+f"(d[42]), "+f"(d[43]), "+f"(d[44]), "+f"(d[45]), "+f"(d[46]), "+f"(d[47]),
      "+f"(d[48]), "+f"(d[49]), "+f"(d[50]), "+f"(d[51]), "+f"(d[52]), "+f"(d[53]), "+f"(d[54]), "+f"(d[55]),
      "+f"(d[56]), "+f"(d[57]), "+f"(d[58]), "+f"(d[59]), "+f"(d[60]), "+f"(d[61]), "+f"(d[62]), "+f"(d[63]),
      "+f"(d[64]), "+f"(d[65]), "+f"(d[66]), "+f"(d[67]), "+f"(d[68]), "+f"(d[69]), "+f"(d[70]), "+f"(d[71]),
      "+f"(d[72]), "+f"(d[73]), "+f"(d[74]), "+f"(d[75]), "+f"(d[76]), "+f"(d[77]), "+f"(d[78]), "+f"(d[79]),
      "+f"(d[80]), "+f"(d[81]), "+f"(d[82]), "+f"(d[83]), "+f"(d[84]), "+f"(d[85]), "+f"(d[86]), "+f"(d[87]),
      "+f"(d[88]), "+f"(d[89]), "+f"(d[90]), "+f"(d[91]), "+f"(d[92]), "+f"(d[93]), "+f"(d[94]), "+f"(d[95])
      : "r"(a[0]), "r"(a[1]), "r"(a[2]), "r"(a[3]), "l"(db), "r"(scale_d), "n"(TB));
}

template <int TA, int TB>
__device__ __forceinline__ void wgmma_ss_n128(float (&d)[64], uint64_t da, uint64_t db, int scale_d) {
  asm volatile(
      "{\n.reg .pred p;\nsetp.ne.b32 p, %66, 0;\n"
      "wgmma.mma_async.sync.aligned.m64n128k16.f32.bf16.bf16 "
      "{%0, %1, %2, %3, %4, %5, %6, %7, %8, %9, %10, %11, %12, %13, %14, %15, %16, %17, %18, %19, %20, %21, %22, %23, %24, %25, %26, %27, %28, %29, %30, %31, %32, %33, %34, %35, %36, %37, %38, %39, %40, %41, %42, %43, %44, %45, %46, %47, %48, %49, %50, %51, %52, %53, %54, %55, %56, %57, %58, %59, %60, %61, %62, %63}, "
      "%64, %65, p, 1, 1, %67, %68;\n}\n"
      :
      "+f"(d[0]), "+f"(d[1]), "+f"(d[2]), "+f"(d[3]), "+f"(d[4]), "+f"(d[5]), "+f"(d[6]), "+f"(d[7]),
      "+f"(d[8]), "+f"(d[9]), "+f"(d[10]), "+f"(d[11]), "+f"(d[12]), "+f"(d[13]), "+f"(d[14]), "+f"(d[15]),
      "+f"(d[16]), "+f"(d[17]), "+f"(d[18]), "+f"(d[19]), "+f"(d[20]), "+f"(d[21]), "+f"(d[22]), "+f"(d[23]),
      "+f"(d[24]), "+f"(d[25]), "+f"(d[26]), "+f"(d[27]), "+f"(d[28]), "+f"(d[29]), "+f"(d[30]), "+f"(d[31]),
      "+f"(d[32]), "+f"(d[33]), "+f"(d[34]), "+f"(d[35]), "+f"(d[36]), "+f"(d[37]), "+f"(d[38]), "+f"(d[39]),
      "+f"(d[40]), "+f"(d[41]), "+f"(d[42]), "+f"(d[43]), "+f"(d[44]), "+f"(d[45]), "+f"(d[46]), "+f"(d[47]),
      "+f"(d[48]), "+f"(d[49]), "+f"(d[50]), "+f"(d[51]), "+f"(d[52]), "+f"(d[53]), "+f"(d[54]), "+f"(d[55]),
      "+f"(d[56]), "+f"(d[57]), "+f"(d[58]), "+f"(d[59]), "+f"(d[60]), "+f"(d[61]), "+f"(d[62]), "+f"(d[63])
      : "l"(da), "l"(db), "r"(scale_d), "n"(TA), "n"(TB));
}

template <int TA, int TB>
__device__ __forceinline__ void wgmma_ss_n64(float (&d)[32], uint64_t da, uint64_t db, int scale_d) {
  asm volatile(
      "{\n.reg .pred p;\nsetp.ne.b32 p, %34, 0;\n"
      "wgmma.mma_async.sync.aligned.m64n64k16.f32.bf16.bf16 "
      "{%0, %1, %2, %3, %4, %5, %6, %7, %8, %9, %10, %11, %12, %13, %14, %15, %16, %17, %18, %19, %20, %21, %22, %23, %24, %25, %26, %27, %28, %29, %30, %31}, "
      "%32, %33, p, 1, 1, %35, %36;\n}\n"
      :
      "+f"(d[0]), "+f"(d[1]), "+f"(d[2]), "+f"(d[3]), "+f"(d[4]), "+f"(d[5]), "+f"(d[6]), "+f"(d[7]),
      "+f"(d[8]), "+f"(d[9]), "+f"(d[10]), "+f"(d[11]), "+f"(d[12]), "+f"(d[13]), "+f"(d[14]), "+f"(d[15]),
      "+f"(d[16]), "+f"(d[17]), "+f"(d[18]), "+f"(d[19]), "+f"(d[20]), "+f"(d[21]), "+f"(d[22]), "+f"(d[23]),
      "+f"(d[24]), "+f"(d[25]), "+f"(d[26]), "+f"(d[27]), "+f"(d[28]), "+f"(d[29]), "+f"(d[30]), "+f"(d[31])
      : "l"(da), "l"(db), "r"(scale_d), "n"(TA), "n"(TB));
}

__device__ __forceinline__ void ln_stats(const uint32_t (&v)[2][8], float (&m)[2], float (&sd)[2]) {
  float s[2], q[2];
#pragma unroll
  for (int i = 0; i < 2; i++) {
    s[i] = 0.f;
#pragma unroll
    for (int j = 0; j < 8; j++) s[i] += lo_f(v[i][j]) + hi_f(v[i][j]);
  }
#pragma unroll
  for (int o = 16; o; o >>= 1) { s[0] += __shfl_xor_sync(~0u, s[0], o); s[1] += __shfl_xor_sync(~0u, s[1], o); }
#pragma unroll
  for (int i = 0; i < 2; i++) {
    s[i] *= (1.f / D_);
    q[i] = 0.f;
#pragma unroll
    for (int j = 0; j < 8; j++) { float a = lo_f(v[i][j]) - s[i], b = hi_f(v[i][j]) - s[i]; q[i] += a * a + b * b; }
  }
#pragma unroll
  for (int o = 16; o; o >>= 1) { q[0] += __shfl_xor_sync(~0u, q[0], o); q[1] += __shfl_xor_sync(~0u, q[1], o); }
#pragma unroll
  for (int i = 0; i < 2; i++) { m[i] = rbf(s[i]); sd[i] = rbf(sqrtf(rbf(rbf(q[i] * (1.f / D_)) + 1e-5f))); }
}

__device__ __forceinline__ void attn_head(const uint32_t (&q)[4], const uint32_t (&kP)[2], const uint32_t (&k0)[2], const uint32_t (&k1)[2],
                                          const uint32_t (&vP)[2], const uint32_t (&v0)[2], const uint32_t (&v1)[2],
                                          bool p0, bool p1, bool mask_prev, uint32_t (&o)[4]) {
  float sP[4] = {0.f, 0.f, 0.f, 0.f}, s0[4] = {0.f, 0.f, 0.f, 0.f}, s1[4] = {0.f, 0.f, 0.f, 0.f};
  mma16(sP, q[0], q[1], q[2], q[3], kP[0], kP[1]);
  mma16(s0, q[0], q[1], q[2], q[3], k0[0], k0[1]);
  mma16(s1, q[0], q[1], q[2], q[3], k1[0], k1[1]);
  if (mask_prev) { sP[0] = sP[1] = -3997171712.f; }
  uint32_t lA = pack2(p0 ? sP[0] : s0[0], p1 ? sP[1] : s0[1]);
  uint32_t lB = pack2(p0 ? s0[2] : s1[2], p1 ? s0[3] : s1[3]);
  uint32_t mx = hmax2(__byte_perm(lA, lB, 0x5410), __byte_perm(lA, lB, 0x7632));
  mx = hmax2(mx, __shfl_xor_sync(~0u, mx, 1));
  mx = hmax2(mx, __shfl_xor_sync(~0u, mx, 2));
  const float c = 0.25f * 1.4426950408889634f;
  float mA = lo_f(mx), mB = hi_f(mx);
  float eA0 = ex2((lo_f(lA) - mA) * c), eA1 = ex2((hi_f(lA) - mA) * c);
  float eB0 = ex2((lo_f(lB) - mB) * c), eB1 = ex2((hi_f(lB) - mB) * c);
  float sA = eA0 + eA1, sB = eB0 + eB1;
  sA += __shfl_xor_sync(~0u, sA, 1); sB += __shfl_xor_sync(~0u, sB, 1);
  sA += __shfl_xor_sync(~0u, sA, 2); sB += __shfl_xor_sync(~0u, sB, 2);
  float iA = rcp(sA), iB = rcp(sB);
  uint32_t pA = pack2(eA0 * iA, eA1 * iA), pB = pack2(eB0 * iB, eB1 * iB);
  uint32_t msk = (p0 ? 0xffffu : 0u) | (p1 ? 0xffff0000u : 0u);
#pragma unroll
  for (int dh = 0; dh < 2; dh++) {
    float a[4] = {0.f, 0.f, 0.f, 0.f};
    mma16(a, pA & msk, 0u, pA & ~msk, pB & msk, vP[dh], v0[dh]);
    mma8(a, 0u, pB & ~msk, v1[dh]);
    o[dh * 2] = pack2(a[0], a[1]);
    o[dh * 2 + 1] = pack2(a[2], a[3]);
  }
}

__device__ __forceinline__ void gemm_mn(float (&acc)[64], int nsteps, uint32_t sb, int wg, int lane, int& st, uint32_t& ph) {
  const uint32_t bars = sb + BAR_OFF;
  const uint64_t dA = make_desc(sb + wg * 8192, 8192, 1024), dB = make_desc(sb + 16384, 8192, 1024);
  int prev = 0;
  for (int it = 0; it < nsteps; it++) {
    mbar_wait(bars + B_FULL + 8 * st, ph);
    wg_fence();
    const uint64_t off = (uint64_t)(st * (SLOT >> 4));
#pragma unroll
    for (int k = 0; k < 4; k++) wgmma_ss_n128<1, 1>(acc, dA + off + k * 128, dB + off + k * 128, (it | k) != 0);
    wg_commit();
    wg_wait<1>();
    if (it > 0 && lane == 0) mbar_arrive(bars + B_EMPTY + 8 * prev);
    prev = st;
    if (++st == NSTG) { st = 0; ph ^= 1; }
  }
  wg_wait<0>();
  if (lane == 0) mbar_arrive(bars + B_EMPTY + 8 * prev);
}

__device__ __forceinline__ void pair_reduce(float (&acc)[64], uint32_t sb, int warp, int lane, uint32_t peer, uint32_t par) {
  const uint32_t bars = sb + BAR_OFF;
  const uint32_t mine = sb + XB_OFF + warp * 4096 + lane * 16;
  const uint32_t rdst = mapa(mine, peer), rbar = mapa(bars + B_XFULL + 8 * warp, peer);
  if (lane == 0) mbar_expect_tx(bars + B_XFULL + 8 * warp, 4096);
  mbar_wait(bars + B_XFREE, par);
#pragma unroll
  for (int j = 0; j < 8; j++) st_async4(rdst + j * 512, acc[32 + 4 * j], acc[33 + 4 * j], acc[34 + 4 * j], acc[35 + 4 * j], rbar);
  mbar_wait(bars + B_XFULL + 8 * warp, par);
#pragma unroll
  for (int j = 0; j < 8; j++) {
    uint4 t = lds128(mine + j * 512);
    acc[4 * j] += __uint_as_float(t.x); acc[4 * j + 1] += __uint_as_float(t.y);
    acc[4 * j + 2] += __uint_as_float(t.z); acc[4 * j + 3] += __uint_as_float(t.w);
  }
}

__device__ __forceinline__ void tile_to_global(uint32_t tile, bf16* base, int pitch, int lane, int first_row) {
#pragma unroll
  for (int i = 0; i < 4; i++) {
    int row = i * 4 + (lane >> 3), ch = lane & 7;
    uint4 v = lds128(tile + row * 128 + ((ch ^ (row & 7)) << 4));
    if (row >= first_row) stg(base + (size_t)row * pitch + ch * 8, v);
  }
}

__global__ void __cluster_dims__(2, 1, 1) __launch_bounds__(384, 1)
fused_kernel(const __grid_constant__ Maps maps, const Ptrs p) {
  extern __shared__ uint8_t smem_raw[];
  const uint32_t sb = (smem_u32(smem_raw) + 1023) & ~1023u;
  const uint32_t bars = sb + BAR_OFF;
  const int tid = threadIdx.x, warp = tid >> 5, lane = tid & 31;
  const int c = blockIdx.x >> 1, r = blockIdx.x & 1;
  int w;
  if (c < 4) w = 4 + c;
  else if (c < 36) w = ((c - 4) & 7) * 8 + ((c - 4) >> 3);
  else w = (1 + (c - 36) % 7) * 8 + 4 + (c - 36) / 7;
  const int G = w >> 3, ti = 2 * G + ((w >> 2) & 1), dj = w & 3, hg = dj * 2 + r, fj = ti - 2;
  const bool has_g1 = G > 0;

  uint32_t xv[2][8];
  if (warp < 8) {
    const bf16* xr = p.x + (size_t)(ti * 128 + hg * 16 + warp * 2) * D_ + lane * 8;
#pragma unroll
    for (int i = 0; i < 2; i++)
#pragma unroll
      for (int j = 0; j < 2; j++) {
        uint4 t = __ldg(reinterpret_cast<const uint4*>(xr + i * D_ + j * 256));
        xv[i][4 * j] = t.x; xv[i][4 * j + 1] = t.y; xv[i][4 * j + 2] = t.z; xv[i][4 * j + 3] = t.w;
      }
  }
  if (tid == 256) {
    PROF_T(0);
    for (int s = 0; s < NSTG; s++) { mbar_init(bars + B_FULL + 8 * s, 1); mbar_init(bars + B_EMPTY + 8 * s, 8); }
    for (int s = 0; s < 8; s++) mbar_init(bars + B_XFULL + 8 * s, 1);
    mbar_init(bars + B_XFREE, 8);
    mbar_init(bars + B_EPOCH, 1);
    asm volatile("fence.mbarrier_init.release.cluster;" ::: "memory");
  }
  __syncthreads();
  asm volatile("barrier.cluster.arrive.relaxed.aligned;" ::: "memory");

  if (warp >= 8) {
    asm volatile("setmaxnreg.dec.sync.aligned.u32 88;");
    if (warp == 8) {
      int st = 0; uint32_t ph = 1;
      auto acquire = [&](uint32_t bytes, uint32_t& fb, uint32_t& dst) {
        mbar_wait(bars + B_EMPTY + 8 * st, ph);
        fb = bars + B_FULL + 8 * st; dst = sb + st * SLOT;
        if (++st == NSTG) { st = 0; ph ^= 1; }
      };
      uint32_t fb, dst;
      for (int j = 0; j < 4; j++) {
        acquire(32768, fb, dst);
        if (elect_one()) {
          mbar_expect_tx(fb, 32768);
#pragma unroll
          for (int q = 0; q < 4; q++) tma2d(dst + q * 8192, &maps.x2, (q & 1) * 512 + j * 128 + (q >> 1) * 64, ti * 64, fb);
        }
        __syncwarp();
#pragma unroll
        for (int h = 0; h < 2; h++) {
          acquire(24576, fb, dst);
          if (elect_one()) {
            mbar_expect_tx(fb, 24576);
#pragma unroll
            for (int q = 0; q < 3; q++) tma2d(dst + q * 8192, &maps.wq, q * 512 + hg * 64, j * 128 + h * 64, fb);
          }
          __syncwarp();
        }
        if (j == 0 && lane == 0) { prefetch_map(&maps.w1); prefetch_map(&maps.h); prefetch_map(&maps.o); prefetch_map(&maps.wo); prefetch_map(&maps.w2); prefetch_map(&maps.u); prefetch_map(&maps.xr); }
      }
      asm volatile("barrier.cluster.wait.acquire.aligned;" ::: "memory");
      mbar_wait(bars + B_EPOCH, 0);
      unsigned ep; asm volatile("ld.shared.u32 %0, [%1];" : "=r"(ep) : "r"(bars + W_EPOCH));
      const int own = dj * 128 + r * 64, oth = dj * 128 + (r ^ 1) * 64;
      if (has_g1) {
        wait_cnt(&g_cnt[r * 32], ep * 64);
        fence_proxy_async();
        if (lane == 0) PROF_T(16);
        for (int it = 0; it < 16; it++) {
          acquire(32768, fb, dst);
          if (elect_one()) {
            const int k = r * 1024 + it * 64;
            mbar_expect_tx(fb, 32768);
            tma2d(dst, &maps.w1, fj * 128, k, fb);
            tma2d(dst + 8192, &maps.w1, fj * 128 + 64, k, fb);
            tma2d(dst + 16384, &maps.h, own, k, fb);
            tma2d(dst + 24576, &maps.h, oth, k, fb);
          }
          __syncwarp();
        }
      }
      wait_cnt(&g_cnt[(2 + ti) * 32], ep * 16);
      fence_proxy_async();
      if (lane == 0) PROF_T(17);
      for (int it = 0; it < 8; it++) {
        acquire(24576, fb, dst);
        if (elect_one()) {
          mbar_expect_tx(fb, 24576);
          tma2d(dst, &maps.o, it * 64, ti * 128, fb);
          tma2d(dst + 16384, &maps.wo, own, it * 64, fb);
        }
        __syncwarp();
      }
      wait_cnt(&g_cnt[(18 + r * 4 + dj) * 32], ep * 14);
      fence_proxy_async();
      if (lane == 0) PROF_T(18);
      for (int it = 0; it < 14; it++) {
        acquire(32768, fb, dst);
        if (elect_one()) {
          const int k = r * 896 + it * 64;
          mbar_expect_tx(fb, 32768);
          tma2d(dst, &maps.w2, ti * 128, k, fb);
          tma2d(dst + 8192, &maps.w2, ti * 128 + 64, k, fb);
          tma2d(dst + 16384, &maps.u, own, k, fb);
          tma2d(dst + 24576, &maps.u, oth, k, fb);
        }
        __syncwarp();
      }
      acquire(16384, fb, dst);
      if (elect_one()) {
        mbar_expect_tx(fb, 16384);
        tma2d(dst, &maps.xr, own, ti * 128, fb);
      }
      __syncwarp();
    } else if (warp == 11) {
      unsigned ep = ld_relaxed(&g_epoch) + 1;
      if (lane == 0) { asm volatile("st.shared.u32 [%0], %1;" ::"r"(bars + W_EPOCH), "r"(ep) : "memory"); mbar_arrive(bars + B_EPOCH); }
      asm volatile("barrier.cluster.wait.acquire.aligned;" ::: "memory");
      bar_sync(1, 288);
      if (lane == 0) { fence_gpu(); red_add(&g_cnt[(ti >> 3) * 32], 1); PROF_T(20); }
      const int cta = blockIdx.x;
      if (lane < 14) prefetch_l2(reinterpret_cast<const char*>(p.w1) + (size_t)cta * 57344 + lane * 4096, 4096);
      if (lane == 14) prefetch_l2(reinterpret_cast<const char*>(p.wo) + (size_t)cta * 4096, 4096);
      bar_sync(9, 288);
      if (lane < 14) prefetch_l2(reinterpret_cast<const char*>(p.w2) + (size_t)cta * 57344 + lane * 4096, 4096);
      if (has_g1) {
        bar_sync(8, 288);
        if (lane == 0) { fence_gpu(); red_add(&g_cnt[(18 + (fj >= 7) * 4 + dj) * 32], 1); PROF_T(21); }
      }
      if (blockIdx.x == 0) {
        bar_sync(10, 288);
        if (lane == 0) st_relaxed(&g_epoch, ep);
      }
    } else {
      const int par = warp - 9;
      asm volatile("barrier.cluster.wait.acquire.aligned;" ::: "memory");
      mbar_wait(bars + B_EPOCH, 0);
      unsigned ep; asm volatile("ld.shared.u32 %0, [%1];" : "=r"(ep) : "r"(bars + W_EPOCH));
      bar_sync(2 + par, 96);
      if (lane == 0) { fence_gpu(); st_relaxed(&g_hflag[(ti * 8 + hg) * 2 + par], ep); }
      uint32_t hp[16], pk[24];
      if (ti > 0) {
        const unsigned* fl = &g_hflag[((ti - 1) * 8 + hg) * 2 + par];
        int it = 0;
        while (ld_acquire(fl) != ep) { if (++it > SPIN_LIMIT) __trap(); }
        const uint4* src = &g_halo[(((ti - 1) * 8 + hg) * 2 + par) * 128 + lane];
#pragma unroll
        for (int j = 0; j < 4; j++) { uint4 t = ldg_cg(src + j * 32); hp[4 * j] = t.x; hp[4 * j + 1] = t.y; hp[4 * j + 2] = t.z; hp[4 * j + 3] = t.w; }
      } else {
#pragma unroll
        for (int j = 0; j < 16; j++) hp[j] = 0u;
      }
      const uint4* src = &g_park[(blockIdx.x * 2 + par) * 192 + lane];
#pragma unroll
      for (int j = 0; j < 6; j++) { uint4 t = ldg_cg(src + j * 32); pk[4 * j] = t.x; pk[4 * j + 1] = t.y; pk[4 * j + 2] = t.z; pk[4 * j + 3] = t.w; }
      const int r0 = lane >> 2, q2 = (lane & 3) * 2;
      bf16* orow = g_o + (size_t)(ti * 128 + 2 * r0 + par) * D_ + hg * 64 + q2;
#pragma unroll
      for (int h = 0; h < 4; h++) {
        const uint32_t q[4] = {pk[2 * h], 0u, pk[2 * h + 1], 0u};
        const uint32_t kP[2] = {hp[2 * h], hp[2 * h + 1]}, k0[2] = {pk[8 + 2 * h], pk[9 + 2 * h]}, z[2] = {0u, 0u};
        const uint32_t vP[2] = {hp[8 + 2 * h], hp[9 + 2 * h]}, v0[2] = {pk[16 + 2 * h], pk[17 + 2 * h]};
        uint32_t o[4];
        attn_head(q, kP, k0, z, vP, v0, z, q2 > r0, q2 + 1 > r0, ti == 0, o);
        *reinterpret_cast<uint32_t*>(orow + h * 16) = o[0];
        *reinterpret_cast<uint32_t*>(orow + h * 16 + 8) = o[2];
      }
      bar_sync(4 + par, 160);
      if (lane == 0) { fence_gpu(); red_add(&g_cnt[(2 + ti) * 32], 1); PROF_T(22 + par); }
    }
  } else {
    asm volatile("setmaxnreg.inc.sync.aligned.u32 208;");
    const int wg = warp >> 2, w4 = warp & 3, r0 = lane >> 2, q2 = (lane & 3) * 2;
    const uint32_t peer = r ^ 1;
    unsigned ep;
    {
      float m[2], sd[2];
      ln_stats(xv, m, sd);
      if (tid == 0) PROF_T(1);
      mbar_wait(bars + B_EPOCH, 0);
      asm volatile("ld.shared.u32 %0, [%1];" : "=r"(ep) : "r"(bars + W_EPOCH));
      const int row = ti * 128 + hg * 16 + warp * 2;
      if (lane < 2) {
        const uint32_t ms = pack2(lane ? m[1] : m[0], lane ? sd[1] : sd[0]);
        st_relaxed64(&g_stats[row + lane], ((unsigned long long)ep << 32) | ms);
      }
#pragma unroll
      for (int i = 0; i < 2; i++) {
        const uint32_t m2 = pack2(m[i], m[i]); const float rs = 1.f / sd[i];
#pragma unroll
        for (int j = 0; j < 8; j++) xv[i][j] = norm2(xv[i][j], m2, rs);
      }
      ln_stats(xv, m, sd);
#pragma unroll
      for (int i = 0; i < 2; i++) {
        const uint32_t m2 = pack2(m[i], m[i]); const float rs = 1.f / sd[i];
#pragma unroll
        for (int j = 0; j < 8; j++) xv[i][j] = norm2(xv[i][j], m2, rs);
        bf16* hr = g_h + (size_t)(row + i) * D_ + lane * 8;
        stg(hr, make_uint4(xv[i][0], xv[i][1], xv[i][2], xv[i][3]));
        stg(hr + 256, make_uint4(xv[i][4], xv[i][5], xv[i][6], xv[i][7]));
      }
      bar_arrive(1, 288);
    }
    uint32_t mA2, mB2; float rsA, rsB;
    {
      const unsigned long long* sp = &g_stats[ti * 128 + 2 * (w4 * 16 + r0) + wg];
      unsigned long long a, b; int it = 0;
      do { a = ld_relaxed64(sp); b = ld_relaxed64(sp + 16); if (++it > SPIN_LIMIT) __trap(); } while ((unsigned)(a >> 32) != ep || (unsigned)(b >> 32) != ep);
      mA2 = __byte_perm((uint32_t)a, 0, 0x1010); rsA = 1.f / hi_f((uint32_t)a);
      mB2 = __byte_perm((uint32_t)b, 0, 0x1010); rsB = 1.f / hi_f((uint32_t)b);
      __syncwarp();
    }
    if (tid == 0) PROF_T(2);
    {
      float acc[96];
      uint32_t af[2][4][4];
      const int arow = w4 * 16 + (lane & 7) + ((lane >> 3) & 1) * 8;
      const uint32_t abase = sb + wg * 8192 + arow * 128;
      auto prep = [&](int s, uint32_t (&a)[4][4]) {
        const int n = 3 * (s >> 1), stg_ = n % NSTG;
        if ((s & 1) == 0) mbar_wait(bars + B_FULL + 8 * stg_, (n / NSTG) & 1);
#pragma unroll
        for (int k = 0; k < 4; k++) ldsm4(abase + stg_ * SLOT + (s & 1) * 16384 + (((2 * k + (lane >> 4)) ^ (arow & 7)) << 4), a[k]);
#pragma unroll
        for (int k = 0; k < 4; k++) {
          a[k][0] = norm2(a[k][0], mA2, rsA); a[k][1] = norm2(a[k][1], mB2, rsB);
          a[k][2] = norm2(a[k][2], mA2, rsA); a[k][3] = norm2(a[k][3], mB2, rsB);
        }
        if (s & 1) { __syncwarp(); if (lane == 0) mbar_arrive(bars + B_EMPTY + 8 * stg_); }
      };
      prep(0, af[0]);
      if (tid == 0) PROF_T(3);
#pragma unroll
      for (int s = 0; s < 8; s++) {
        const int n = 3 * (s >> 1) + 1 + (s & 1), stg_ = n % NSTG;
        mbar_wait(bars + B_FULL + 8 * stg_, (n / NSTG) & 1);
        wg_fence();
        const uint64_t dB = make_desc(sb + stg_ * SLOT, 8192, 1024);
#pragma unroll
        for (int k = 0; k < 4; k++) wgmma_rs_n192<1>(acc, af[s & 1][k], dB + k * 128, (s | k) != 0);
        wg_commit();
        if (s < 7) wg_wait<1>(); else wg_wait<0>();
        if (s > 0 && lane == 0) mbar_arrive(bars + B_EMPTY + 8 * ((3 * ((s - 1) >> 1) + 1 + ((s - 1) & 1)) % NSTG));
        if (s < 7) prep(s + 1, af[(s + 1) & 1]);
      }
      if (lane == 0) mbar_arrive(bars + B_EMPTY + 8 * (11 % NSTG));
      bar_arrive(9, 288);
      if (tid == 0) PROF_T(4);

      uint32_t pq[8][2], pk[8][2], pv[8][2];
#pragma unroll
      for (int j = 0; j < 8; j++) {
        pq[j][0] = pack2(acc[4 * j], acc[4 * j + 1]);           pq[j][1] = pack2(acc[4 * j + 2], acc[4 * j + 3]);
        pk[j][0] = pack2(acc[32 + 4 * j], acc[33 + 4 * j]);     pk[j][1] = pack2(acc[34 + 4 * j], acc[35 + 4 * j]);
        pv[j][0] = movm(pack2(acc[64 + 4 * j], acc[65 + 4 * j])); pv[j][1] = movm(pack2(acc[66 + 4 * j], acc[67 + 4 * j]));
      }
      const uint32_t xbw = sb + XB_OFF + warp * 4096;
      if (w4 < 3) {
        sts128(xbw + lane * 16, pk[0][1], pk[1][1], pk[2][1], pk[3][1]);
        sts128(xbw + 512 + lane * 16, pk[4][1], pk[5][1], pk[6][1], pk[7][1]);
        sts128(xbw + 1024 + lane * 16, pv[0][1], pv[1][1], pv[2][1], pv[3][1]);
        sts128(xbw + 1536 + lane * 16, pv[4][1], pv[5][1], pv[6][1], pv[7][1]);
      } else {
        uint4* dst = &g_halo[((ti * 8 + hg) * 2 + wg) * 128 + lane];
        stg(dst, make_uint4(pk[0][1], pk[1][1], pk[2][1], pk[3][1]));
        stg(dst + 32, make_uint4(pk[4][1], pk[5][1], pk[6][1], pk[7][1]));
        stg(dst + 64, make_uint4(pv[0][1], pv[1][1], pv[2][1], pv[3][1]));
        stg(dst + 96, make_uint4(pv[4][1], pv[5][1], pv[6][1], pv[7][1]));
        bar_arrive(2 + wg, 96);
      }
      if (w4 == 0) {
        uint4* dst = &g_park[(blockIdx.x * 2 + wg) * 192 + lane];
        stg(dst, make_uint4(pq[0][0], pq[1][0], pq[2][0], pq[3][0]));
        stg(dst + 32, make_uint4(pq[4][0], pq[5][0], pq[6][0], pq[7][0]));
        stg(dst + 64, make_uint4(pk[0][0], pk[1][0], pk[2][0], pk[3][0]));
        stg(dst + 96, make_uint4(pk[4][0], pk[5][0], pk[6][0], pk[7][0]));
        stg(dst + 128, make_uint4(pv[0][0], pv[1][0], pv[2][0], pv[3][0]));
        stg(dst + 160, make_uint4(pv[4][0], pv[5][0], pv[6][0], pv[7][0]));
        bar_arrive(2 + wg, 96);
      }
      bar_sync(6 + wg, 128);
      uint32_t hp[16];
      if (w4 > 0) {
#pragma unroll
        for (int j = 0; j < 4; j++) { uint4 t = lds128(xbw - 4096 + j * 512 + lane * 16); hp[4 * j] = t.x; hp[4 * j + 1] = t.y; hp[4 * j + 2] = t.z; hp[4 * j + 3] = t.w; }
      } else {
#pragma unroll
        for (int j = 0; j < 16; j++) hp[j] = 0u;
      }
      const int srow = (lane & 7) + ((lane >> 3) & 1) * 8;
#pragma unroll
      for (int h = 0; h < 4; h++) {
        const uint32_t q[4] = {pq[2 * h][0], pq[2 * h][1], pq[2 * h + 1][0], pq[2 * h + 1][1]};
        const uint32_t kP[2] = {hp[2 * h], hp[2 * h + 1]}, k0[2] = {pk[2 * h][0], pk[2 * h + 1][0]}, k1[2] = {pk[2 * h][1], pk[2 * h + 1][1]};
        const uint32_t vP[2] = {hp[8 + 2 * h], hp[9 + 2 * h]}, v0[2] = {pv[2 * h][0], pv[2 * h + 1][0]}, v1[2] = {pv[2 * h][1], pv[2 * h + 1][1]};
        uint32_t o[4];
        attn_head(q, kP, k0, k1, vP, v0, v1, q2 > r0, q2 + 1 > r0, false, o);
        stsm4(xbw + 2048 + srow * 128 + (((2 * h + (lane >> 4)) ^ (srow & 7)) << 4), o[0], o[1], o[2], o[3]);
      }
      __syncwarp();
      tile_to_global(xbw + 2048, g_o + (size_t)(ti * 128 + w4 * 32 + wg) * D_ + hg * 64, 2 * D_, lane, w4 == 0 ? 8 : 0);
      bar_arrive(4 + wg, 160);
      asm volatile("barrier.cluster.wait.acquire.aligned;" ::: "memory");
      __syncwarp();
      if (lane == 0) mbar_arrive_remote(mapa(bars + B_XFREE, peer));
    }
    if (tid == 0) PROF_T(5);
    int st = 0; uint32_t ph = 0, xpar = 0;
    const int trow = wg * 64 + w4 * 16;
    const int srow = (lane & 7) + ((lane >> 3) & 1) * 8;
    const int own = dj * 128 + r * 64;
    if (has_g1) {
      float acc[64];
      const uint32_t bA = __bfloat16_as_ushort(p.b1[fj * 128 + trow + r0]) * 0x10001u, bB = __bfloat16_as_ushort(p.b1[fj * 128 + trow + r0 + 8]) * 0x10001u;
      gemm_mn(acc, 16, sb, wg, lane, st, ph);
      if (tid == 0) PROF_T(6);
      pair_reduce(acc, sb, warp, lane, peer, xpar);
      xpar ^= 1;
      if (tid == 0) PROF_T(7);
      uint32_t u[16];
#pragma unroll
      for (int j = 0; j < 16; j++) {
        const uint32_t t = hadd2(pack2(acc[2 * j], acc[2 * j + 1]), (j & 1) ? bB : bA);
        const float a = lo_f(t), b = hi_f(t);
        const float k0 = 0.7978845608028654f, k1 = 0.7978845608028654f * 0.044715f;
        const float ta = tanh_(a * fmaf(k1, a * a, k0)), tb = tanh_(b * fmaf(k1, b * b, k0));
        const float ha = 0.5f * a, hb = 0.5f * b;
        u[j] = pack2(fmaf(ha, ta, ha), fmaf(hb, tb, hb));
      }
      const uint32_t xbw = sb + XB_OFF + warp * 4096;
      __syncwarp();
#pragma unroll
      for (int j = 0; j < 4; j++) stsm4(xbw + srow * 128 + (((2 * j + (lane >> 4)) ^ (srow & 7)) << 4), u[4 * j], u[4 * j + 1], u[4 * j + 2], u[4 * j + 3]);
      __syncwarp();
      tile_to_global(xbw, g_u + (size_t)(fj * 128 + trow) * D_ + own, D_, lane, 0);
      bar_arrive(8, 288);
      __syncwarp();
      if (lane == 0) mbar_arrive_remote(mapa(bars + B_XFREE, peer));
      if (tid == 0) PROF_T(8);
    }
    float sacc[32];
    {
      const uint64_t dA = make_desc(sb + wg * 8192, 16, 1024), dB = make_desc(sb + 16384, 8192, 1024);
      int prev = 0;
      for (int it = 0; it < 8; it++) {
        mbar_wait(bars + B_FULL + 8 * st, ph);
        wg_fence();
        const uint64_t off = (uint64_t)(st * (SLOT >> 4));
#pragma unroll
        for (int k = 0; k < 4; k++) wgmma_ss_n64<0, 1>(sacc, dA + off + k * 2, dB + off + k * 128, (it | k) != 0);
        wg_commit();
        wg_wait<1>();
        if (it > 0 && lane == 0) mbar_arrive(bars + B_EMPTY + 8 * prev);
        prev = st;
        if (++st == NSTG) { st = 0; ph ^= 1; }
      }
      wg_wait<0>();
      if (lane == 0) mbar_arrive(bars + B_EMPTY + 8 * prev);
    }
    if (tid == 0) PROF_T(9);
    {
      float acc[64];
      const uint32_t bA = __bfloat16_as_ushort(p.b2[ti * 128 + trow + r0]) * 0x10001u, bB = __bfloat16_as_ushort(p.b2[ti * 128 + trow + r0 + 8]) * 0x10001u;
      uint32_t sp[16];
#pragma unroll
      for (int j = 0; j < 16; j++) sp[j] = pack2(sacc[2 * j], sacc[2 * j + 1]);
      gemm_mn(acc, 14, sb, wg, lane, st, ph);
      if (tid == 0) PROF_T(10);
      if (blockIdx.x == 0) bar_arrive(10, 288);
      pair_reduce(acc, sb, warp, lane, peer, xpar);
      if (tid == 0) PROF_T(11);
      mbar_wait(bars + B_FULL + 8 * st, ph);
      const uint32_t tile = sb + st * SLOT + trow * 128;
#pragma unroll
      for (int j = 0; j < 4; j++) {
        const uint32_t a = tile + srow * 128 + (((2 * j + (lane >> 4)) ^ (srow & 7)) << 4);
        uint32_t xf[4];
        ldsm4(a, xf);
#pragma unroll
        for (int i = 0; i < 4; i++) {
          const int e = 4 * j + i;
          const uint32_t t = hadd2(pack2(acc[2 * e], acc[2 * e + 1]), (i & 1) ? bB : bA);
          const float ha = 0.5f * lo_f(t), hb = 0.5f * hi_f(t);
          const uint32_t g = pack2(fmaf(ha, tanh_(ha), ha), fmaf(hb, tanh_(hb), hb));
          xf[i] = hadd2(xf[i], hmul2(sp[e], g));
        }
        stsm4(a, xf[0], xf[1], xf[2], xf[3]);
      }
      __syncwarp();
      tile_to_global(tile, p.out + (size_t)(ti * 128 + trow) * D_ + own, D_, lane, 0);
      if (tid == 0) PROF_T(12);
    }
  }
}

typedef CUresult (*EncodeFn)(CUtensorMap*, CUtensorMapDataType, cuuint32_t, void*, const cuuint64_t*, const cuuint64_t*, const cuuint32_t*,
                             const cuuint32_t*, CUtensorMapInterleave, CUtensorMapSwizzle, CUtensorMapL2promotion, CUtensorMapFloatOOBfill);

void make_map(EncodeFn enc, CUtensorMap* m, const void* ptr, uint64_t cols, uint64_t rows, uint32_t box_rows) {
  cuuint64_t gd[2] = {cols, rows};
  cuuint64_t gs[1] = {cols * 2};
  cuuint32_t bd[2] = {64, box_rows};
  cuuint32_t es[2] = {1, 1};
  CUresult r = enc(m, CU_TENSOR_MAP_DATA_TYPE_BFLOAT16, 2, const_cast<void*>(ptr), gd, gs, bd, es, CU_TENSOR_MAP_INTERLEAVE_NONE,
                   CU_TENSOR_MAP_SWIZZLE_128B, CU_TENSOR_MAP_L2_PROMOTION_L2_128B, CU_TENSOR_MAP_FLOAT_OOB_FILL_NONE);
  if (r != CUDA_SUCCESS) fprintf(stderr, "cuTensorMapEncodeTiled failed: %d\n", (int)r);
}

}

extern "C" void kernel_launch(void* const* d_in, const int* in_sizes, int n_in, void* d_out, int out_size) {
  (void)in_sizes; (void)n_in; (void)out_size;
  const bf16* x = (const bf16*)d_in[0];
  const bf16* wqkv = (const bf16*)d_in[1];
  const bf16* wo = (const bf16*)d_in[2];
  const bf16* w1 = (const bf16*)d_in[4];
  const bf16* b1 = (const bf16*)d_in[5];
  const bf16* w2 = (const bf16*)d_in[6];
  const bf16* b2 = (const bf16*)d_in[7];
  EncodeFn enc = nullptr;
  cudaDriverEntryPointQueryResult qr;
  cudaGetDriverEntryPoint("cuTensorMapEncodeTiled", (void**)&enc, cudaEnableDefault, &qr);
  void *h, *u, *o;
  cudaGetSymbolAddress(&h, g_h);
  cudaGetSymbolAddress(&u, g_u);
  cudaGetSymbolAddress(&o, g_o);
  Maps m;
  make_map(enc, &m.x2, x, 2 * D_, S_ / 2, 64);
  make_map(enc, &m.wq, wqkv, 3 * D_, D_, 64);
  make_map(enc, &m.w1, w1, F_, S_, 64);
  make_map(enc, &m.h, h, D_, S_, 64);
  make_map(enc, &m.o, o, D_, S_, 128);
  make_map(enc, &m.wo, wo, D_, D_, 64);
  make_map(enc, &m.w2, w2, S_, F_, 64);
  make_map(enc, &m.u, u, D_, F_, 64);
  make_map(enc, &m.xr, x, D_, S_, 128);
  Ptrs p{x, b1, b2, w1, w2, wo, (bf16*)d_out};
  cudaFuncSetAttribute(fused_kernel, cudaFuncAttributeMaxDynamicSharedMemorySize, SMEM_BYTES);
  fused_kernel<<<128, 384, SMEM_BYTES>>>(m, p);
}
```

```cpp
#include <cuda_runtime.h>
#include <cuda_bf16.h>
#include <cuda.h>
#include <stdint.h>
#include <stdio.h>

namespace {

typedef __nv_bfloat16 bf16;
constexpr int S_ = 2048, D_ = 512, F_ = 1792;
constexpr int NSTG = 6, SLOT = 32768;
constexpr int R_OFF = NSTG * SLOT;
constexpr int T_OFF = R_OFF + 16384;
constexpr int BAR_OFF = T_OFF + 16384;
constexpr int SMEM_BYTES = BAR_OFF + 768 + 1024;
constexpr int B_FULL = 0, B_EMPTY = 48, B_XFULL = 96, B_SFULL = 160, B_HOK = 224, B_UOK = 288, B_OOK = 344, B_XFREE = 352, B_EPOCH = 360,
              B_GO = 368, W_EPOCH = 376, B_XFULL2 = 384;
constexpr int SPIN_LIMIT = 1 << 17;

struct Maps { CUtensorMap x2, wq, w1, h, o, wo, w2, u, xr; };
struct Ptrs { const bf16 *x, *b1, *b2, *w1, *w2, *wo, *wq; bf16* out; uint32_t zero; };

__device__ __align__(1024) bf16 g_h[S_ * D_];
__device__ __align__(1024) bf16 g_u[F_ * D_];
__device__ __align__(1024) bf16 g_o[S_ * D_];
struct Sync {
  unsigned cnt[32 * 32];
  unsigned long long stats[S_];
  uint4 halo[16 * 8 * 2 * 6 * 32];
};
__device__ __align__(1024) Sync g_s;

__device__ __forceinline__ uint32_t smem_u32(const void* p) { return (uint32_t)__cvta_generic_to_shared(p); }
__device__ __forceinline__ void mbar_init(uint32_t b, uint32_t c) { asm volatile("mbarrier.init.shared::cta.b64 [%0], %1;" ::"r"(b), "r"(c) : "memory"); }
__device__ __forceinline__ void mbar_expect_tx(uint32_t b, uint32_t n) { asm volatile("mbarrier.arrive.expect_tx.shared::cta.b64 _, [%0], %1;" ::"r"(b), "r"(n) : "memory"); }
__device__ __forceinline__ void mbar_arrive(uint32_t b) { asm volatile("mbarrier.arrive.shared::cta.b64 _, [%0];" ::"r"(b) : "memory"); }
__device__ __forceinline__ void mbar_arrive_remote(uint32_t rb) { asm volatile("mbarrier.arrive.shared::cluster.b64 _, [%0];" ::"r"(rb) : "memory"); }
__device__ __forceinline__ bool mbar_try(uint32_t b, uint32_t par) {
  uint32_t ok;
  asm volatile("{\n.reg .pred p;\nmbarrier.try_wait.parity.shared::cta.b64 p, [%1], %2;\nselp.u32 %0, 1, 0, p;\n}" : "=r"(ok) : "r"(b), "r"(par) : "memory");
  return ok;
}
__device__ __forceinline__ void mbar_wait(uint32_t b, uint32_t par) {
  if (mbar_try(b, par)) return;
  int it = 0;
#pragma unroll 1
  while (!mbar_try(b, par)) { if (++it > SPIN_LIMIT) break; }
}
__device__ __forceinline__ uint32_t mapa(uint32_t a, uint32_t cta) { uint32_t r; asm("mapa.shared::cluster.u32 %0, %1, %2;" : "=r"(r) : "r"(a), "r"(cta)); return r; }
__device__ __forceinline__ void tma2d(uint32_t dst, const CUtensorMap* m, int c0, int c1, uint32_t bar) {
  asm volatile("cp.async.bulk.tensor.2d.shared::cluster.global.mbarrier::complete_tx::bytes [%0], [%1, {%3, %4}], [%2];"
               ::"r"(dst), "l"(m), "r"(bar), "r"(c0), "r"(c1) : "memory");
}
__device__ __forceinline__ void prefetch_map(const CUtensorMap* m) { asm volatile("prefetch.tensormap [%0];" ::"l"(m) : "memory"); }
__device__ __forceinline__ void prefetch_l2(const void* p, uint32_t bytes) { asm volatile("cp.async.bulk.prefetch.L2.global [%0], %1;" ::"l"(p), "r"(bytes) : "memory"); }
__device__ __forceinline__ bool elect_one() { uint32_t p; asm volatile("{\n.reg .pred P;\nelect.sync _|P, 0xffffffff;\nselp.u32 %0, 1, 0, P;\n}" : "=r"(p)); return p; }
__device__ __forceinline__ void bar_arrive(int id, int n) { asm volatile("bar.arrive %0, %1;" ::"r"(id), "r"(n) : "memory"); }
__device__ __forceinline__ void bar_sync(int id, int n) { asm volatile("bar.sync %0, %1;" ::"r"(id), "r"(n) : "memory"); }
__device__ __forceinline__ void wg_fence() { asm volatile("wgmma.fence.sync.aligned;" ::: "memory"); }
__device__ __forceinline__ void wg_commit() { asm volatile("wgmma.commit_group.sync.aligned;" ::: "memory"); }
template <int N> __device__ __forceinline__ void wg_wait() { asm volatile("wgmma.wait_group.sync.aligned %0;" ::"n"(N) : "memory"); }
template <int N> __device__ __forceinline__ void fence_regs(float (&a)[N]) {
#pragma unroll
  for (int i = 0; i < N; i++) asm volatile("" : "+f"(a[i])::"memory");
}
__device__ __forceinline__ uint64_t make_desc(uint32_t addr, uint32_t lbo, uint32_t sbo) {
  return (uint64_t)(((addr & 0x3FFFF) >> 4) | ((lbo >> 4) << 16)) | ((uint64_t)((sbo >> 4) | (1u << 30)) << 32);
}
__device__ __forceinline__ void fence_release() { asm volatile("fence.release.gpu;" ::: "memory"); }
__device__ __forceinline__ void fence_proxy_async() { asm volatile("fence.proxy.async.global;" ::: "memory"); }
__device__ __forceinline__ void red_add(unsigned* p, unsigned v) { asm volatile("red.relaxed.gpu.global.add.u32 [%0], %1;" ::"l"(p), "r"(v) : "memory"); }
__device__ __forceinline__ unsigned ld_relaxed(const unsigned* p) { unsigned v; asm volatile("ld.relaxed.gpu.global.u32 %0, [%1];" : "=r"(v) : "l"(p) : "memory"); return v; }
__device__ __forceinline__ void st_relaxed(unsigned* p, unsigned v) { asm volatile("st.relaxed.gpu.global.u32 [%0], %1;" ::"l"(p), "r"(v) : "memory"); }
__device__ __forceinline__ void watch(const unsigned* p, int n, unsigned target, uint32_t bar, int lane, int sleep_ns) {
  bool done = lane >= n;
  const unsigned* q = p + (done ? 0 : lane);
  for (int it = 0; it < SPIN_LIMIT; it++) {
    const unsigned v = ld_relaxed(q);
    if (!done && (int)(v - target) >= 0) { asm volatile("fence.acquire.gpu;" ::: "memory"); mbar_arrive(bar + 8 * lane); done = true; }
    if (__all_sync(~0u, done)) break;
    if (sleep_ns) __nanosleep(sleep_ns);
  }
}
__device__ __forceinline__ unsigned long long ld_relaxed64(const unsigned long long* p) { unsigned long long v; asm volatile("ld.relaxed.gpu.global.u64 %0, [%1];" : "=l"(v) : "l"(p) : "memory"); return v; }
__device__ __forceinline__ void st_relaxed64(unsigned long long* p, unsigned long long v) { asm volatile("st.relaxed.gpu.global.u64 [%0], %1;" ::"l"(p), "l"(v) : "memory"); }
__device__ __forceinline__ void st_pkt(void* p, uint32_t a, uint32_t b, uint32_t c, uint32_t tag) {
  asm volatile("{\n.reg .b128 v;\n.reg .b64 l, h;\nmov.b64 l, {%1, %2};\nmov.b64 h, {%3, %4};\nmov.b128 v, {l, h};\nst.relaxed.gpu.global.b128 [%0], v;\n}"
               ::"l"(p), "r"(a), "r"(b), "r"(c), "r"(tag) : "memory");
}
__device__ __forceinline__ void ld_pkt(const void* p, uint32_t& a, uint32_t& b, uint32_t& c, uint32_t& tag) {
  asm volatile("{\n.reg .b128 v;\n.reg .b64 l, h;\nld.relaxed.gpu.global.b128 v, [%4];\nmov.b128 {l, h}, v;\nmov.b64 {%0, %1}, l;\nmov.b64 {%2, %3}, h;\n}"
               : "=r"(a), "=r"(b), "=r"(c), "=r"(tag) : "l"(p) : "memory");
}
__device__ __forceinline__ uint32_t ldg_u16(const void* p) { uint32_t v; asm volatile("ld.global.nc.u16 %0, [%1];" : "=r"(v) : "l"(p)); return v; }
__device__ __forceinline__ void stg(void* p, uint4 v) { asm volatile("st.global.v4.u32 [%0], {%1,%2,%3,%4};" ::"l"(p), "r"(v.x), "r"(v.y), "r"(v.z), "r"(v.w) : "memory"); }
__device__ __forceinline__ uint4 lds128(uint32_t a) { uint4 v; asm volatile("ld.shared.v4.u32 {%0,%1,%2,%3}, [%4];" : "=r"(v.x), "=r"(v.y), "=r"(v.z), "=r"(v.w) : "r"(a) : "memory"); return v; }
__device__ __forceinline__ void sts128(uint32_t a, uint32_t x, uint32_t y, uint32_t z, uint32_t w) { asm volatile("st.shared.v4.u32 [%0], {%1,%2,%3,%4};" ::"r"(a), "r"(x), "r"(y), "r"(z), "r"(w) : "memory"); }
__device__ __forceinline__ void ldsm4(uint32_t a, uint32_t (&r)[4]) { asm volatile("ldmatrix.sync.aligned.m8n8.x4.shared.b16 {%0,%1,%2,%3}, [%4];" : "=r"(r[0]), "=r"(r[1]), "=r"(r[2]), "=r"(r[3]) : "r"(a) : "memory"); }
__device__ __forceinline__ void stsm4(uint32_t a, uint32_t r0, uint32_t r1, uint32_t r2, uint32_t r3) { asm volatile("stmatrix.sync.aligned.m8n8.x4.shared.b16 [%0], {%1,%2,%3,%4};" ::"r"(a), "r"(r0), "r"(r1), "r"(r2), "r"(r3) : "memory"); }
__device__ __forceinline__ void st_async4(uint32_t ra, uint32_t a, uint32_t b, uint32_t c, uint32_t d, uint32_t rbar) {
  asm volatile("st.async.weak.shared::cluster.mbarrier::complete_tx::bytes.v4.b32 [%0], {%1,%2,%3,%4}, [%5];" ::"r"(ra), "r"(a), "r"(b), "r"(c), "r"(d), "r"(rbar) : "memory");
}
__device__ __forceinline__ uint32_t movm(uint32_t a) { uint32_t d; asm("movmatrix.sync.aligned.m8n8.trans.b16 %0, %1;" : "=r"(d) : "r"(a)); return d; }
__device__ __forceinline__ void mma16(float (&c)[4], uint32_t a0, uint32_t a1, uint32_t a2, uint32_t a3, uint32_t b0, uint32_t b1) {
  asm("mma.sync.aligned.m16n8k16.row.col.f32.bf16.bf16.f32 {%0,%1,%2,%3}, {%4,%5,%6,%7}, {%8,%9}, {%0,%1,%2,%3};"
               : "+f"(c[0]), "+f"(c[1]), "+f"(c[2]), "+f"(c[3]) : "r"(a0), "r"(a1), "r"(a2), "r"(a3), "r"(b0), "r"(b1));
}
__device__ __forceinline__ uint32_t pack2(float lo, float hi) { uint32_t d; asm("cvt.rn.bf16x2.f32 %0, %1, %2;" : "=r"(d) : "f"(hi), "f"(lo)); return d; }
__device__ __forceinline__ float lo_f(uint32_t v) { return __uint_as_float(v << 16); }
__device__ __forceinline__ float hi_f(uint32_t v) { return __uint_as_float(v & 0xffff0000u); }
__device__ __forceinline__ float rbf(float v) { return __bfloat162float(__float2bfloat16_rn(v)); }
__device__ __forceinline__ uint32_t hadd2(uint32_t a, uint32_t b) { uint32_t d; asm("add.rn.bf16x2 %0, %1, %2;" : "=r"(d) : "r"(a), "r"(b)); return d; }
__device__ __forceinline__ uint32_t hsub2(uint32_t a, uint32_t b) { uint32_t d; asm("sub.rn.bf16x2 %0, %1, %2;" : "=r"(d) : "r"(a), "r"(b)); return d; }
__device__ __forceinline__ uint32_t hmul2(uint32_t a, uint32_t b) { uint32_t d; asm("mul.rn.bf16x2 %0, %1, %2;" : "=r"(d) : "r"(a), "r"(b)); return d; }
__device__ __forceinline__ uint32_t hfma2(uint32_t a, uint32_t b, uint32_t c) { uint32_t d; asm("fma.rn.bf16x2 %0, %1, %2, %3;" : "=r"(d) : "r"(a), "r"(b), "r"(c)); return d; }
__device__ __forceinline__ uint32_t hmax2(uint32_t a, uint32_t b) { uint32_t d; asm("max.bf16x2 %0, %1, %2;" : "=r"(d) : "r"(a), "r"(b)); return d; }
__device__ __forceinline__ float ex2(float x) { float y; asm("ex2.approx.ftz.f32 %0, %1;" : "=f"(y) : "f"(x)); return y; }
__device__ __forceinline__ float rcp(float x) { float y; asm("rcp.approx.ftz.f32 %0, %1;" : "=f"(y) : "f"(x)); return y; }
__device__ __forceinline__ float sqrt_(float x) { float y; asm("sqrt.approx.ftz.f32 %0, %1;" : "=f"(y) : "f"(x)); return y; }
__device__ __forceinline__ float tanh_(float x) { float y; asm("tanh.approx.f32 %0, %1;" : "=f"(y) : "f"(x)); return y; }
__device__ __forceinline__ uint32_t half2x(uint32_t b) { uint32_t d; asm volatile("{\n.reg .b32 t;\nprmt.b32 t, %1, %1, 0x1010;\nmul.rn.bf16x2 %0, t, %2;\n}" : "=r"(d) : "r"(b), "r"(0x3f003f00u)); return d; }
struct Norm { uint32_t m, hi, lo; };
__device__ __forceinline__ Norm make_norm(float m, float sd) {
  const float rs = rcp(sd), hi = rbf(rs);
  return Norm{pack2(m, m), pack2(hi, hi), pack2(rs - hi, rs - hi)};
}
__device__ __forceinline__ uint32_t norm2(uint32_t x, const Norm& n) {
  const uint32_t t = hsub2(x, n.m);
  return hfma2(t, n.hi, hmul2(t, n.lo));
}

template <int TB>
__device__ __forceinline__ void wgmma_rs_n192(float (&d)[96], const uint32_t (&a)[4], uint64_t db, int scale_d) {
  asm volatile(
      "{\n.reg .pred p;\nsetp.ne.b32 p, %101, 0;\n"
      "wgmma.mma_async.sync.aligned.m64n192k16.f32.bf16.bf16 "
      "{%0, %1, %2, %3, %4, %5, %6, %7, %8, %9, %10, %11, %12, %13, %14, %15, %16, %17, %18, %19, %20, %21, %22, %23, %24, %25, %26, %27, %28, %29, %30, %31, %32, %33, %34, %35, %36, %37, %38, %39, %40, %41, %42, %43, %44, %45, %46, %47, %48, %49, %50, %51, %52, %53, %54, %55, %56, %57, %58, %59, %60, %61, %62, %63, %64, %65, %66, %67, %68, %69, %70, %71, %72, %73, %74, %75, %76, %77, %78, %79, %80, %81, %82, %83, %84, %85, %86, %87, %88, %89, %90, %91, %92, %93, %94, %95}, "
      "{%96, %97, %98, %99}, %100, p, 1, 1, %102;\n}\n"
      :
      "+f"(d[0]), "+f"(d[1]), "+f"(d[2]), "+f"(d[3]), "+f"(d[4]), "+f"(d[5]), "+f"(d[6]), "+f"(d[7]),
      "+f"(d[8]), "+f"(d[9]), "+f"(d[10]), "+f"(d[11]), "+f"(d[12]), "+f"(d[13]), "+f"(d[14]), "+f"(d[15]),
      "+f"(d[16]), "+f"(d[17]), "+f"(d[18]), "+f"(d[19]), "+f"(d[20]), "+f"(d[21]), "+f"(d[22]), "+f"(d[23]),
      "+f"(d[24]), "+f"(d[25]), "+f"(d[26]), "+f"(d[27]), "+f"(d[28]), "+f"(d[29]), "+f"(d[30]), "+f"(d[31]),
      "+f"(d[32]), "+f"(d[33]), "+f"(d[34]), "+f"(d[35]), "+f"(d[36]), "+f"(d[37]), "+f"(d[38]), "+f"(d[39]),
      "+f"(d[40]), "+f"(d[41]), "+f"(d[42]), "+f"(d[43]), "+f"(d[44]), "+f"(d[45]), "+f"(d[46]), "+f"(d[47]),
      "+f"(d[48]), "+f"(d[49]), "+f"(d[50]), "+f"(d[51]), "+f"(d[52]), "+f"(d[53]), "+f"(d[54]), "+f"(d[55]),
      "+f"(d[56]), "+f"(d[57]), "+f"(d[58]), "+f"(d[59]), "+f"(d[60]), "+f"(d[61]), "+f"(d[62]), "+f"(d[63]),
      "+f"(d[64]), "+f"(d[65]), "+f"(d[66]), "+f"(d[67]), "+f"(d[68]), "+f"(d[69]), "+f"(d[70]), "+f"(d[71]),
      "+f"(d[72]), "+f"(d[73]), "+f"(d[74]), "+f"(d[75]), "+f"(d[76]), "+f"(d[77]), "+f"(d[78]), "+f"(d[79]),
      "+f"(d[80]), "+f"(d[81]), "+f"(d[82]), "+f"(d[83]), "+f"(d[84]), "+f"(d[85]), "+f"(d[86]), "+f"(d[87]),
      "+f"(d[88]), "+f"(d[89]), "+f"(d[90]), "+f"(d[91]), "+f"(d[92]), "+f"(d[93]), "+f"(d[94]), "+f"(d[95])
      : "r"(a[0]), "r"(a[1]), "r"(a[2]), "r"(a[3]), "l"(db), "r"(scale_d), "n"(TB));
}

template <int TA, int TB>
__device__ __forceinline__ void wgmma_ss_n128(float (&d)[64], uint64_t da, uint64_t db, int scale_d) {
  asm volatile(
      "{\n.reg .pred p;\nsetp.ne.b32 p, %66, 0;\n"
      "wgmma.mma_async.sync.aligned.m64n128k16.f32.bf16.bf16 "
      "{%0, %1, %2, %3, %4, %5, %6, %7, %8, %9, %10, %11, %12, %13, %14, %15, %16, %17, %18, %19, %20, %21, %22, %23, %24, %25, %26, %27, %28, %29, %30, %31, %32, %33, %34, %35, %36, %37, %38, %39, %40, %41, %42, %43, %44, %45, %46, %47, %48, %49, %50, %51, %52, %53, %54, %55, %56, %57, %58, %59, %60, %61, %62, %63}, "
      "%64, %65, p, 1, 1, %67, %68;\n}\n"
      :
      "+f"(d[0]), "+f"(d[1]), "+f"(d[2]), "+f"(d[3]), "+f"(d[4]), "+f"(d[5]), "+f"(d[6]), "+f"(d[7]),
      "+f"(d[8]), "+f"(d[9]), "+f"(d[10]), "+f"(d[11]), "+f"(d[12]), "+f"(d[13]), "+f"(d[14]), "+f"(d[15]),
      "+f"(d[16]), "+f"(d[17]), "+f"(d[18]), "+f"(d[19]), "+f"(d[20]), "+f"(d[21]), "+f"(d[22]), "+f"(d[23]),
      "+f"(d[24]), "+f"(d[25]), "+f"(d[26]), "+f"(d[27]), "+f"(d[28]), "+f"(d[29]), "+f"(d[30]), "+f"(d[31]),
      "+f"(d[32]), "+f"(d[33]), "+f"(d[34]), "+f"(d[35]), "+f"(d[36]), "+f"(d[37]), "+f"(d[38]), "+f"(d[39]),
      "+f"(d[40]), "+f"(d[41]), "+f"(d[42]), "+f"(d[43]), "+f"(d[44]), "+f"(d[45]), "+f"(d[46]), "+f"(d[47]),
      "+f"(d[48]), "+f"(d[49]), "+f"(d[50]), "+f"(d[51]), "+f"(d[52]), "+f"(d[53]), "+f"(d[54]), "+f"(d[55]),
      "+f"(d[56]), "+f"(d[57]), "+f"(d[58]), "+f"(d[59]), "+f"(d[60]), "+f"(d[61]), "+f"(d[62]), "+f"(d[63])
      : "l"(da), "l"(db), "r"(scale_d), "n"(TA), "n"(TB));
}


__device__ __forceinline__ void ln_stats(const uint32_t (&v)[2][8], float (&m)[2], float (&sd)[2]) {
  float s[2], q[2];
#pragma unroll
  for (int i = 0; i < 2; i++) {
    float t[4];
#pragma unroll
    for (int j = 0; j < 4; j++) t[j] = (lo_f(v[i][2 * j]) + hi_f(v[i][2 * j])) + (lo_f(v[i][2 * j + 1]) + hi_f(v[i][2 * j + 1]));
    s[i] = ((t[0] + t[1]) + (t[2] + t[3])) * (1.f / 16);
    float q0 = 0.f, q1 = 0.f;
#pragma unroll
    for (int j = 0; j < 8; j++) { const float a = lo_f(v[i][j]) - s[i], b = hi_f(v[i][j]) - s[i]; q0 = fmaf(a, a, q0); q1 = fmaf(b, b, q1); }
    q[i] = q0 + q1;
  }
#pragma unroll
  for (int o = 1; o < 32; o <<= 1) {
#pragma unroll
    for (int i = 0; i < 2; i++) {
      const float s2 = __shfl_xor_sync(~0u, s[i], o), q2 = __shfl_xor_sync(~0u, q[i], o), d = s2 - s[i];
      q[i] = fmaf(d * d, 8.f * o, q[i] + q2);
      s[i] = 0.5f * (s[i] + s2);
    }
  }
#pragma unroll
  for (int i = 0; i < 2; i++) { m[i] = rbf(s[i]); sd[i] = rbf(sqrt_(rbf(rbf(q[i] * (1.f / D_)) + 1e-5f))); }
}

__device__ __forceinline__ void ln_stats_unit(const uint32_t (&v)[2][8], float (&m)[2], float (&sd)[2]) {
  float s[2], q[2];
#pragma unroll
  for (int i = 0; i < 2; i++) {
    float s0 = 0.f, s1 = 0.f, q0 = 0.f, q1 = 0.f;
#pragma unroll
    for (int j = 0; j < 8; j++) { const float a = lo_f(v[i][j]), b = hi_f(v[i][j]); s0 += a; s1 += b; q0 = fmaf(a, a, q0); q1 = fmaf(b, b, q1); }
    s[i] = s0 + s1; q[i] = q0 + q1;
  }
#pragma unroll
  for (int o = 1; o < 32; o <<= 1) {
#pragma unroll
    for (int i = 0; i < 2; i++) { s[i] += __shfl_xor_sync(~0u, s[i], o); q[i] += __shfl_xor_sync(~0u, q[i], o); }
  }
#pragma unroll
  for (int i = 0; i < 2; i++) {
    const float mean = s[i] * (1.f / D_), var = fmaxf(fmaf(-mean, mean, q[i] * (1.f / D_)), 0.f);
    m[i] = rbf(mean);
    sd[i] = rbf(sqrt_(rbf(rbf(var) + 1e-5f)));
  }
}

__device__ __forceinline__ void softmax4(const uint32_t (&l)[4], uint32_t (&pr)[4]) {
  uint32_t m01 = hmax2(__byte_perm(l[0], l[1], 0x5410), __byte_perm(l[0], l[1], 0x7632));
  uint32_t m23 = hmax2(__byte_perm(l[2], l[3], 0x5410), __byte_perm(l[2], l[3], 0x7632));
  m01 = hmax2(m01, __shfl_xor_sync(~0u, m01, 1)); m23 = hmax2(m23, __shfl_xor_sync(~0u, m23, 1));
  m01 = hmax2(m01, __shfl_xor_sync(~0u, m01, 2)); m23 = hmax2(m23, __shfl_xor_sync(~0u, m23, 2));
  const float mx[4] = {lo_f(m01), hi_f(m01), lo_f(m23), hi_f(m23)};
  const float c = 0.25f * 1.4426950408889634f;
  float e[4][2], s[4];
#pragma unroll
  for (int h = 0; h < 4; h++) { e[h][0] = ex2((lo_f(l[h]) - mx[h]) * c); e[h][1] = ex2((hi_f(l[h]) - mx[h]) * c); s[h] = e[h][0] + e[h][1]; }
#pragma unroll
  for (int h = 0; h < 4; h++) s[h] += __shfl_xor_sync(~0u, s[h], 1);
#pragma unroll
  for (int h = 0; h < 4; h++) s[h] += __shfl_xor_sync(~0u, s[h], 2);
#pragma unroll
  for (int h = 0; h < 4; h++) { const float i = rcp(s[h]); pr[h] = pack2(e[h][0] * i, e[h][1] * i); }
}

template <int V> struct IC { static constexpr int value = V; };
struct Ring {
  int st; uint32_t ph;
  __device__ __forceinline__ void next() { if (++st == NSTG) { st = 0; ph ^= 1; } }
};

template <int TA>
__device__ __forceinline__ void gemm_step(float (&acc)[64], bool first, uint32_t sb, int wg, int lane, Ring& rg, int& prev) {
  const uint32_t bars = sb + BAR_OFF;
  const uint64_t dA = make_desc(sb + wg * 8192, TA ? 8192 : 16, 1024), dB = make_desc(sb + 16384, 8192, 1024);
  mbar_wait(bars + B_FULL + 8 * rg.st, rg.ph);
  wg_fence();
  const uint64_t off = (uint64_t)(rg.st * (SLOT >> 4));
#pragma unroll
  for (int k = 0; k < 4; k++) wgmma_ss_n128<TA, 1>(acc, dA + off + k * (TA ? 128 : 2), dB + off + k * 128, !(first && k == 0));
  wg_commit();
  wg_wait<1>();
  if (prev >= 0 && lane == 0) mbar_arrive(bars + B_EMPTY + 8 * prev);
  prev = rg.st;
  rg.next();
}

__device__ __forceinline__ void pair_send(const float (&acc)[64], uint32_t sb, int warp, int lane, uint32_t peer, int j0, int j1, int buf, int xb, int expect) {
  const uint32_t bar = sb + BAR_OFF + xb + 8 * warp;
  if (expect && lane == 0) mbar_expect_tx(bar, expect);
  const uint32_t dst = mapa(sb + buf + warp * 2048 + lane * 16, peer), rbar = mapa(bar, peer);
#pragma unroll
  for (int j = j0; j < j1; j++)
    st_async4(dst + j * 512, pack2(acc[32 + 8 * j], acc[33 + 8 * j]), pack2(acc[34 + 8 * j], acc[35 + 8 * j]),
              pack2(acc[36 + 8 * j], acc[37 + 8 * j]), pack2(acc[38 + 8 * j], acc[39 + 8 * j]), rbar);
}
__device__ __forceinline__ void pair_recv(float (&acc)[64], uint32_t sb, int warp, int lane, uint32_t par, int buf, int xb) {
  mbar_wait(sb + BAR_OFF + xb + 8 * warp, par);
  const uint32_t mine = sb + buf + warp * 2048 + lane * 16;
#pragma unroll
  for (int j = 0; j < 4; j++) {
    const uint4 t = lds128(mine + j * 512);
    acc[8 * j] += lo_f(t.x); acc[8 * j + 1] += hi_f(t.x); acc[8 * j + 2] += lo_f(t.y); acc[8 * j + 3] += hi_f(t.y);
    acc[8 * j + 4] += lo_f(t.z); acc[8 * j + 5] += hi_f(t.z); acc[8 * j + 6] += lo_f(t.w); acc[8 * j + 7] += hi_f(t.w);
  }
}
__device__ __forceinline__ void tile_to_global(uint32_t tile, bf16* base, int pitch, int lane) {
#pragma unroll
  for (int i = 0; i < 4; i++) {
    const int row = i * 4 + (lane >> 3), ch = lane & 7;
    stg(base + (size_t)row * pitch + ch * 8, lds128(tile + row * 128 + ((ch ^ (row & 7)) << 4)));
  }
}

__global__ void __cluster_dims__(2, 1, 1) __launch_bounds__(384, 1)
fused_kernel(const Ptrs p, const __grid_constant__ Maps maps) {
  const uint32_t tstart = (uint32_t)clock();
  extern __shared__ uint8_t smem_raw[];
  const uint32_t sb = (smem_u32(smem_raw) + 1023) & ~1023u;
  const uint32_t bars = sb + BAR_OFF;
  const int tid = threadIdx.x, warp = __shfl_sync(~0u, tid >> 5, 0), lane = tid & 31;
  const int wgi = __shfl_sync(~0u, tid >> 7, 0);
  const int c = blockIdx.x >> 1, r = blockIdx.x & 1;
  int w;
  if (c < 4) w = 4 + c;
  else if (c < 36) w = ((c - 4) & 7) * 8 + ((c - 4) >> 3);
  else w = (1 + (c - 36) % 7) * 8 + 4 + (c - 36) / 7;
  const int G = w >> 3, ti = 2 * G + ((w >> 2) & 1), dj = w & 3, fj = ti - 2;
  const int tq = 4 * (G >> 1) + ((w >> 1) & 3), hg = (G & 1) * 4 + (w & 1) * 2 + r;
  const bool has_g1 = G > 0;

  uint32_t xv[2][8];
  if (warp < 8) {
    const bf16* xr = p.x + (size_t)(tq * 128 + hg * 16 + warp * 2) * D_ + lane * 8;
#pragma unroll
    for (int i = 0; i < 2; i++)
#pragma unroll
      for (int j = 0; j < 2; j++) {
        uint4 t = __ldg(reinterpret_cast<const uint4*>(xr + i * D_ + j * 256));
        xv[i][4 * j] = t.x; xv[i][4 * j + 1] = t.y; xv[i][4 * j + 2] = t.z; xv[i][4 * j + 3] = t.w;
      }
  }
  if (warp == 11 && lane < 8) st_pkt(&g_s.stats[tq * 128 + hg * 16 + lane * 2], 0u, 0u, 0u, 0u);
  if (tid == 256) {
    prefetch_map(&maps.x2); prefetch_map(&maps.wq);
#pragma unroll
    for (int s = 0; s < NSTG; s++) { mbar_init(bars + B_FULL + 8 * s, 1); mbar_init(bars + B_EMPTY + 8 * s, 8); }
#pragma unroll
    for (int s = 0; s < 8; s++) { mbar_init(bars + B_XFULL + 8 * s, 1); mbar_init(bars + B_SFULL + 8 * s, 1); mbar_init(bars + B_HOK + 8 * s, 1); mbar_init(bars + B_UOK + 8 * s, 1); }
#pragma unroll
    for (int s = 0; s < 8; s++) mbar_init(bars + B_XFULL2 + 8 * s, 1);
    mbar_init(bars + B_XFREE, 1);
    mbar_init(bars + B_EPOCH, 1);
    mbar_init(bars + B_GO, 8);
    asm volatile("fence.mbarrier_init.release.cluster;" ::: "memory");
  }
  __syncthreads();
  asm volatile("barrier.cluster.arrive.relaxed.aligned;" ::: "memory");

  if (wgi == 2) {
    asm volatile("setmaxnreg.dec.sync.aligned.u32 40;");
    if (warp == 8) {
      Ring rg{0, 1};
      uint32_t fb, dst;
      auto acquire = [&]() {
        mbar_wait(bars + B_EMPTY + 8 * rg.st, rg.ph);
        fb = bars + B_FULL + 8 * rg.st; dst = sb + rg.st * SLOT;
        rg.next();
      };
      auto load_x = [&](int j) {
        acquire();
        if (elect_one()) {
          mbar_expect_tx(fb, 32768);
#pragma unroll
          for (int q = 0; q < 4; q++) tma2d(dst + q * 8192, &maps.x2, (q & 1) * 512 + j * 128 + (q >> 1) * 64, tq * 64, fb);
        }
        __syncwarp();
      };
      auto load_w = [&](int s) {
        acquire();
        if (elect_one()) {
          mbar_expect_tx(fb, 24576);
#pragma unroll
          for (int q = 0; q < 3; q++) tma2d(dst + q * 8192, &maps.wq, q * 512 + hg * 64, s * 64, fb);
        }
        __syncwarp();
      };
      const int own = dj * 128 + r * 64, oth = dj * 128 + (r ^ 1) * 64;
      auto load_wgt = [&](const CUtensorMap* mw, int m0, int k) {
        acquire();
        if (elect_one()) {
          mbar_expect_tx(fb, 32768);
          tma2d(dst, mw, m0, k, fb);
          tma2d(dst + 8192, mw, m0 + 64, k, fb);
        }
        __syncwarp();
      };
      auto load_act = [&](const CUtensorMap* ma, int st, int k) {
        if (elect_one()) {
          tma2d(sb + st * SLOT + 16384, ma, own, k, bars + B_FULL + 8 * st);
          tma2d(sb + st * SLOT + 24576, ma, oth, k, bars + B_FULL + 8 * st);
        }
        __syncwarp();
      };
      auto wait_ok = [&](uint32_t bar) { mbar_wait(bar, 0); fence_proxy_async(); };

      load_x(0); load_w(0); load_w(1); load_x(1); load_w(2); load_w(3);
      if (lane == 0) { prefetch_map(&maps.w1); prefetch_map(&maps.h); prefetch_map(&maps.o); prefetch_map(&maps.wo); prefetch_map(&maps.w2); prefetch_map(&maps.u); prefetch_map(&maps.xr); }
      asm volatile("barrier.cluster.wait.acquire.aligned;" ::: "memory");
      load_x(2); load_w(4);
      if (has_g1) {
        const int k0 = r * 1024;
        Ring r0 = rg;
        load_wgt(&maps.w1, fj * 128, k0); load_wgt(&maps.w1, fj * 128, k0 + 64);
        wait_ok(bars + B_HOK);
        load_act(&maps.h, r0.st, k0); r0.next(); load_act(&maps.h, r0.st, k0 + 64);
        for (int it = 2; it < 16; it++) {
          if (it == 14) load_x(3);
          if ((it & 1) == 0) wait_ok(bars + B_HOK + 4 * it);
          const int st = rg.st;
          load_wgt(&maps.w1, fj * 128, k0 + it * 64);
          load_act(&maps.h, st, k0 + it * 64);
        }
      } else load_x(3);
      load_w(5); load_w(6); load_w(7);
      {
        const int k0 = r * 896;
        Ring r0 = rg;
        if (has_g1) {
          rg.next();
          for (int it = 1; it < 4; it++) load_wgt(&maps.w2, ti * 128, k0 + it * 64);
          const Ring q = rg;
          rg = r0; load_wgt(&maps.w2, ti * 128, k0); rg = q;
        } else {
          for (int it = 0; it < 4; it++) load_wgt(&maps.w2, ti * 128, k0 + it * 64);
        }
        load_wgt(&maps.w2, ti * 128, k0 + 256); load_wgt(&maps.w2, ti * 128, k0 + 320);
        uint32_t t0 = 0;
        for (int it = 0; it < 6; it++) {
          if (it == 1) t0 = (uint32_t)clock();
          if (it >= 1) while ((uint32_t)clock() - t0 < (uint32_t)(it * 420)) {}
          if ((it & 1) == 0) wait_ok(bars + B_UOK + 4 * it);
          load_act(&maps.u, r0.st, k0 + it * 64);
          r0.next();
        }
        for (int it = 6; it < 14; it++) {
          if ((it & 1) == 0) wait_ok(bars + B_UOK + 4 * it);
          const int st = rg.st;
          load_wgt(&maps.w2, ti * 128, k0 + it * 64);
          load_act(&maps.u, st, k0 + it * 64);
        }
      }
      wait_ok(bars + B_OOK);
      for (int it = 0; it < 4; it++) {
        acquire();
        if (elect_one()) {
          mbar_expect_tx(fb, 32768);
          tma2d(dst, &maps.o, r * 256 + it * 64, ti * 128, fb);
          tma2d(dst + 16384, &maps.wo, own, r * 256 + it * 64, fb);
          tma2d(dst + 24576, &maps.wo, oth, r * 256 + it * 64, fb);
        }
        __syncwarp();
      }
      acquire();
      if (elect_one()) {
        mbar_expect_tx(fb, 16384);
        tma2d(dst, &maps.xr, own, ti * 128, fb);
      }
      __syncwarp();
    } else if (warp == 9) {
      const unsigned ep = ld_relaxed(&g_s.cnt[31 * 32]) + 1;
      if (lane == 0) { asm volatile("st.shared.u32 [%0], %1;" ::"r"(bars + W_EPOCH), "r"(ep) : "memory"); mbar_arrive(bars + B_EPOCH); }
      asm volatile("barrier.cluster.wait.acquire.aligned;" ::: "memory");
      bar_sync(1, 288);
      if (lane == 0) { fence_release(); red_add(&g_s.cnt[(tq >> 3) * 32 + (tq & 7)], 1); }
      __syncwarp();
      if (has_g1) {
        bar_sync(2, 288);
        if (lane == 0) { fence_release(); red_add(&g_s.cnt[(18 + (fj >= 7) * 4 + dj) * 32 + fj % 7], 1); }
        __syncwarp();
      }
      bar_sync(3, 288);
      if (lane == 0) {
        mbar_arrive_remote(mapa(bars + B_XFREE, r ^ 1));
        fence_release();
        red_add(&g_s.cnt[(2 + tq) * 32 + (hg >> 2)], 1);
      }
      __syncwarp();
      if (blockIdx.x == 0) {
        bar_sync(4, 288);
        if (lane == 0) st_relaxed(&g_s.cnt[31 * 32], ep);
      }
    } else if (warp == 10) {
      asm volatile("barrier.cluster.wait.acquire.aligned;" ::: "memory");
      mbar_wait(bars + B_EPOCH, 0);
      unsigned ep; asm volatile("ld.shared.u32 %0, [%1];" : "=r"(ep) : "r"(bars + W_EPOCH));
      if (has_g1) {
        mbar_wait(bars + B_GO, 0);
        watch(&g_s.cnt[r * 32], 8, ep * 8, bars + B_HOK, lane, 0);
        bar_sync(5, 288);
      }
      watch(&g_s.cnt[(18 + r * 4 + dj) * 32], 7, ep * 2, bars + B_UOK, lane, 0);
      { const uint32_t t0 = (uint32_t)clock(); while ((uint32_t)clock() - t0 < 3500u) __nanosleep(100); }
      watch(&g_s.cnt[(2 + ti) * 32 + r], 1, ep * 4, bars + B_OOK, lane, 100);
    } else {
      asm volatile("barrier.cluster.wait.acquire.aligned;" ::: "memory");
      if (lane == 0) {
        const int b = blockIdx.x, row = b & 63, half = b >> 6;
        __nanosleep(1200);
        prefetch_l2(p.wq + (size_t)(256 + 2 * b) * (3 * D_), 2 * 3 * D_ * 2);
        mbar_wait(bars + B_GO, 0);
        __nanosleep(1100);
        for (int j = 3; j < 16; j++) { prefetch_l2(p.w1 + (size_t)(half * 1024 + j * 64 + row) * F_, F_ * 2); __nanosleep(200); }
        for (int j = 0; j < 14; j++) { prefetch_l2(p.w2 + (size_t)(half * 896 + j * 64 + row) * S_, S_ * 2); __nanosleep(200); }
        prefetch_l2(p.wo + (size_t)(4 * b) * D_, 4 * D_ * 2);
      }
    }
  } else {
    asm volatile("setmaxnreg.inc.sync.aligned.u32 232;");
    const int wg = warp >> 2, r0 = lane >> 2, q2 = (lane & 3) * 2;
    const int w4 = (warp & 3) ^ (wg * 2);
    const uint32_t peer = r ^ 1;
    const uint32_t b1A = ldg_u16(p.b1 + (has_g1 ? fj : 0) * 128 + warp * 16 + r0), b1B = ldg_u16(p.b1 + (has_g1 ? fj : 0) * 128 + warp * 16 + r0 + 8);
    const uint32_t b2A = ldg_u16(p.b2 + ti * 128 + warp * 16 + r0), b2B = ldg_u16(p.b2 + ti * 128 + warp * 16 + r0 + 8);
    if (w4 == 3) {
      uint4* dst = &g_s.halo[((tq * 8 + hg) * 2 + wg) * 192 + lane];
#pragma unroll
      for (int j = 0; j < 6; j++) st_pkt(dst + j * 32, 0u, 0u, 0u, 0u);
    }
    const int trow = warp * 16;
    const int srow = (lane & 7) + ((lane >> 3) & 1) * 8;
    const int own = dj * 128 + r * 64;
    const uint32_t rw = sb + R_OFF + warp * 2048, tw = sb + T_OFF + (wg * 4 + w4) * 2048;
    const uint32_t swz = (uint32_t)(srow * 128), sx = (uint32_t)((lane >> 4) ^ (srow & 7));
    const uint32_t abase = sb + (wg * 4 + w4) * 2048 + swz;
    auto release = [&](int st) { if (lane == 0) mbar_arrive(bars + B_EMPTY + 8 * st); };

    unsigned ep;
    Norm nA, nB;
    {
      const int row = tq * 128 + hg * 16 + warp * 2;
      const unsigned long long* sp = &g_s.stats[tq * 128 + 2 * (w4 * 16 + r0) + wg];
      float m[2], sd[2];
      ln_stats(xv, m, sd);
      mbar_wait(bars + B_EPOCH, 0);
      asm volatile("ld.shared.u32 %0, [%1];" : "=r"(ep) : "r"(bars + W_EPOCH));
      if (lane < 2) st_relaxed64(&g_s.stats[row + lane], ((unsigned long long)ep << 32) | pack2(lane ? m[1] : m[0], lane ? sd[1] : sd[0]));
#pragma unroll
      for (int i = 0; i < 2; i++) {
        const Norm nr = make_norm(m[i], sd[i]);
#pragma unroll
        for (int j = 0; j < 8; j++) xv[i][j] = norm2(xv[i][j], nr);
      }
      ln_stats_unit(xv, m, sd);
      while ((uint32_t)clock() - tstart < 3700u) {}
      unsigned long long a = ld_relaxed64(sp), b = ld_relaxed64(sp + 16);
#pragma unroll
      for (int i = 0; i < 2; i++) {
        const Norm nr = make_norm(m[i], sd[i]);
#pragma unroll
        for (int j = 0; j < 8; j++) xv[i][j] = norm2(xv[i][j], nr);
      }
      int it = 0;
      while ((unsigned)(a >> 32) != ep || (unsigned)(b >> 32) != ep) { a = ld_relaxed64(sp); b = ld_relaxed64(sp + 16); if (++it > SPIN_LIMIT) break; }
      __syncwarp();
#pragma unroll
      for (int i = 0; i < 2; i++) {
        bf16* hr = g_h + (size_t)(row + i) * D_ + lane * 8;
        stg(hr, make_uint4(xv[i][0], xv[i][1], xv[i][2], xv[i][3]));
        stg(hr + 256, make_uint4(xv[i][4], xv[i][5], xv[i][6], xv[i][7]));
      }
      bar_arrive(1, 288);
      nA = make_norm(lo_f((uint32_t)a), hi_f((uint32_t)a));
      nB = make_norm(lo_f((uint32_t)b), hi_f((uint32_t)b));
      __syncwarp();
      if (lane == 0) mbar_arrive(bars + B_GO);
    }
    Ring rg{1, 0};
    int prev = -1;
    {
      float acc[96], gac[64];
      uint32_t af[2][4][4];
      auto prep = [&](Ring xs, int half, uint32_t (&a)[4][4]) {
        if (half == 0) mbar_wait(bars + B_FULL + 8 * xs.st, xs.ph);
#pragma unroll
        for (int k = 0; k < 4; k++) ldsm4(abase + xs.st * SLOT + half * 16384 + (((2 * k) ^ sx) << 4), a[k]);
        if (half == 1 && lane == 0) mbar_arrive(bars + B_EMPTY + 8 * xs.st + ((a[0][0] ^ a[1][0] ^ a[2][0] ^ a[3][0]) & p.zero));
#pragma unroll
        for (int k = 0; k < 4; k++) { a[k][0] = norm2(a[k][0], nA); a[k][1] = norm2(a[k][1], nB); a[k][2] = norm2(a[k][2], nA); a[k][3] = norm2(a[k][3], nB); }
      };
      auto step = [&](const uint32_t (&a)[4][4], bool first) {
        mbar_wait(bars + B_FULL + 8 * rg.st, rg.ph);
        const uint64_t dB = make_desc(sb + rg.st * SLOT, 8192, 1024);
        wg_fence();
#pragma unroll
        for (int k = 0; k < 4; k++) wgmma_rs_n192<1>(acc, a[k], dB + k * 128, !(first && k == 0));
        wg_commit();
        wg_wait<1>();
        if (prev >= 0) release(prev);
        prev = rg.st;
        rg.next();
      };
      Ring xs{0, 0};
      prep(xs, 0, af[0]);
      step(af[0], true);  prep(xs, 1, af[1]);
      step(af[1], false); xs = rg; rg.next(); prep(xs, 0, af[0]);
      step(af[0], false); prep(xs, 1, af[1]);
      step(af[1], false); xs = rg; rg.next(); prep(xs, 0, af[0]);
      step(af[0], false); prep(xs, 1, af[1]);
      if (has_g1) {
#pragma unroll 1
        for (int it = 0; it < 14; it++) gemm_step<1>(gac, it == 0, sb, wg, lane, rg, prev);
        xs = rg; rg.next();
        gemm_step<1>(gac, false, sb, wg, lane, rg, prev);
        prep(xs, 0, af[0]);
        gemm_step<1>(gac, false, sb, wg, lane, rg, prev);
      } else {
        wg_wait<0>(); release(prev); prev = -1;
        xs = rg; rg.next();
        prep(xs, 0, af[0]);
      }
      asm volatile("barrier.cluster.wait.acquire.aligned;" ::: "memory");
      mbar_wait(bars + B_FULL + 8 * rg.st, rg.ph);
      const uint64_t dB5 = make_desc(sb + rg.st * SLOT, 8192, 1024);
      auto part5 = [&](auto k0, auto k1) {
        wg_fence();
#pragma unroll
        for (int k = decltype(k0)::value; k < decltype(k1)::value; k++) wgmma_rs_n192<1>(acc, af[1][k], dB5 + k * 128, 1);
        wg_commit();
      };
      part5(IC<0>{}, IC<1>{});
      wg_wait<1>();
      if (prev >= 0) release(prev);
      prev = rg.st;
      rg.next();
      if (has_g1) { fence_regs(gac); pair_send(gac, sb, warp, lane, peer, 0, 2, R_OFF, B_XFULL, 1024); }
      part5(IC<1>{}, IC<3>{});
      if (has_g1) { pair_send(gac, sb, warp, lane, peer, 2, 4, R_OFF, B_XFULL2, 1024); }
      part5(IC<3>{}, IC<4>{});
      if (has_g1) {
        const uint32_t bA = half2x(b1A), bB = half2x(b1B);
        uint32_t u[16];
#pragma unroll
        for (int j = 0; j < 4; j++) {
          if ((j & 1) == 0) mbar_wait(bars + (j ? B_XFULL2 : B_XFULL) + 8 * warp, 0);
          const uint4 t4 = lds128(rw + lane * 16 + j * 512);
          const uint32_t tt[4] = {t4.x, t4.y, t4.z, t4.w};
#pragma unroll
          for (int i = 0; i < 4; i++) {
            const uint32_t t = hfma2(pack2(gac[8 * j + 2 * i] + lo_f(tt[i]), gac[8 * j + 2 * i + 1] + hi_f(tt[i])), 0x3f003f00u, (i & 1) ? bB : bA);
            const float ha = lo_f(t), hb = hi_f(t);
            const float k0 = 2.f * 0.7978845608028654f, k1 = 8.f * 0.7978845608028654f * 0.044715f;
            const float ta = tanh_(ha * fmaf(k1, ha * ha, k0)), tb = tanh_(hb * fmaf(k1, hb * hb, k0));
            u[4 * j + i] = pack2(fmaf(ha, ta, ha), fmaf(hb, tb, hb));
          }
        }
        __syncwarp();
#pragma unroll
        for (int j = 0; j < 4; j++) stsm4(rw + swz + (((2 * j) ^ sx) << 4), u[4 * j], u[4 * j + 1], u[4 * j + 2], u[4 * j + 3]);
        __syncwarp();
        tile_to_global(rw, g_u + (size_t)(fj * 128 + trow) * D_ + own, D_, lane);
        bar_arrive(2, 288); bar_arrive(5, 288);
      }
      step(af[0], false);
      prep(xs, 1, af[1]);
      step(af[1], false);
      uint4* hptr = &g_s.halo[(((w4 == 0 && tq > 0 ? tq - 1 : tq) * 8 + hg) * 2 + wg) * 192 + lane];
      asm volatile("" : "+l"(hptr));
      wg_wait<0>();
      fence_regs(acc);
      release(prev); prev = -1;

      uint32_t pq[8][2], pk[8][2], pv[8][2];
#pragma unroll
      for (int j = 0; j < 8; j++) {
        pk[j][1] = pack2(acc[34 + 4 * j], acc[35 + 4 * j]);
        pv[j][1] = movm(pack2(acc[66 + 4 * j], acc[67 + 4 * j]));
      }
      if (w4 < 3) {
        sts128(tw + lane * 16, pk[0][1], pk[1][1], pk[2][1], pk[3][1]);
        sts128(tw + 512 + lane * 16, pk[4][1], pk[5][1], pk[6][1], pk[7][1]);
        sts128(tw + 1024 + lane * 16, pv[0][1], pv[1][1], pv[2][1], pv[3][1]);
        sts128(tw + 1536 + lane * 16, pv[4][1], pv[5][1], pv[6][1], pv[7][1]);
      } else {
        st_pkt(hptr, pk[0][1], pk[1][1], pk[2][1], ep);
        st_pkt(hptr + 32, pk[3][1], pk[4][1], pk[5][1], ep);
        st_pkt(hptr + 64, pk[6][1], pk[7][1], pv[0][1], ep);
        st_pkt(hptr + 96, pv[1][1], pv[2][1], pv[3][1], ep);
        st_pkt(hptr + 128, pv[4][1], pv[5][1], pv[6][1], ep);
        st_pkt(hptr + 160, pv[7][1], 0u, 0u, ep);
      }
#pragma unroll
      for (int j = 0; j < 8; j++) {
        pq[j][0] = pack2(acc[4 * j], acc[4 * j + 1]); pq[j][1] = pack2(acc[4 * j + 2], acc[4 * j + 3]);
        pk[j][0] = pack2(acc[32 + 4 * j], acc[33 + 4 * j]);
        pv[j][0] = movm(pack2(acc[64 + 4 * j], acc[65 + 4 * j]));
      }
      const bool p0 = q2 > r0, p1 = q2 + 1 > r0;
      const uint32_t msk = (p0 ? 0xffffu : 0u) | (p1 ? 0xffff0000u : 0u);
      uint32_t hp[18], l[4], pr[4];
      float sA[4][2], oacc[8][4];
#pragma unroll
      for (int h = 0; h < 4; h++) {
        float s0[4] = {}, s1[4] = {};
        mma16(s0, pq[2 * h][0], pq[2 * h][1], pq[2 * h + 1][0], pq[2 * h + 1][1], pk[2 * h][0], pk[2 * h + 1][0]);
        mma16(s1, pq[2 * h][0], pq[2 * h][1], pq[2 * h + 1][0], pq[2 * h + 1][1], pk[2 * h][1], pk[2 * h + 1][1]);
        sA[h][0] = s0[0]; sA[h][1] = s0[1];
        l[h] = pack2(p0 ? s0[2] : s1[2], p1 ? s0[3] : s1[3]);
      }
      softmax4(l, pr);
#pragma unroll
      for (int j = 0; j < 8; j++) {
        oacc[j][0] = oacc[j][1] = oacc[j][2] = oacc[j][3] = 0.f;
        mma16(oacc[j], 0u, pr[j >> 1] & msk, 0u, pr[j >> 1] & ~msk, pv[j][0], pv[j][1]);
      }
      bar_sync(6 + wg, 128);
      if (w4 > 0) {
#pragma unroll
        for (int j = 0; j < 4; j++) { const uint4 t = lds128(tw - 2048 + j * 512 + lane * 16); hp[4 * j] = t.x; hp[4 * j + 1] = t.y; hp[4 * j + 2] = t.z; hp[4 * j + 3] = t.w; }
      } else if (tq > 0) {
        bool ok; int it = 0;
        do {
          ok = true;
#pragma unroll
          for (int j = 0; j < 6; j++) { uint32_t tag; ld_pkt(hptr + j * 32, hp[3 * j], hp[3 * j + 1], hp[3 * j + 2], tag); ok = ok && tag == ep; }
          if (++it > SPIN_LIMIT) break;
        } while (!ok);
        __syncwarp();
      } else {
#pragma unroll
        for (int j = 0; j < 16; j++) hp[j] = 0u;
      }
#pragma unroll
      for (int h = 0; h < 4; h++) {
        float sP[4] = {};
        mma16(sP, pq[2 * h][0], pq[2 * h][1], pq[2 * h + 1][0], pq[2 * h + 1][1], hp[2 * h], hp[2 * h + 1]);
        if (w4 == 0 && tq == 0) sP[0] = sP[1] = -3997171712.f;
        l[h] = pack2(p0 ? sP[0] : sA[h][0], p1 ? sP[1] : sA[h][1]);
      }
      softmax4(l, pr);
#pragma unroll
      for (int j = 0; j < 8; j++) mma16(oacc[j], pr[j >> 1] & msk, 0u, pr[j >> 1] & ~msk, 0u, hp[8 + j], pv[j][0]);
      __syncwarp();
#pragma unroll
      for (int h = 0; h < 4; h++)
        stsm4(rw + swz + (((2 * h) ^ sx) << 4), pack2(oacc[2 * h][0], oacc[2 * h][1]), pack2(oacc[2 * h][2], oacc[2 * h][3]),
              pack2(oacc[2 * h + 1][0], oacc[2 * h + 1][1]), pack2(oacc[2 * h + 1][2], oacc[2 * h + 1][3]));
      __syncwarp();
      tile_to_global(rw, g_o + (size_t)(tq * 128 + w4 * 32 + wg) * D_ + hg * 64, 2 * D_, lane);
      bar_arrive(3, 288);
    }
    {
      float acc[64], sac[64];
#pragma unroll 1
      for (int it = 0; it < 14; it++) gemm_step<1>(acc, it == 0, sb, wg, lane, rg, prev);
      if (blockIdx.x == 0) bar_arrive(4, 288);
      gemm_step<0>(sac, true, sb, wg, lane, rg, prev);
      fence_regs(acc);
      mbar_wait(bars + B_XFREE, 0);
      pair_send(acc, sb, warp, lane, peer, 0, 2, R_OFF, B_XFULL, 2048);
      prev = -1;
      gemm_step<0>(sac, false, sb, wg, lane, rg, prev);
      pair_send(acc, sb, warp, lane, peer, 2, 4, R_OFF, B_XFULL, 0);
      prev = -1;
      gemm_step<0>(sac, false, sb, wg, lane, rg, prev);
      prev = -1;
      gemm_step<0>(sac, false, sb, wg, lane, rg, prev);
      pair_recv(acc, sb, warp, lane, has_g1 ? 1 : 0, R_OFF, B_XFULL);
      wg_wait<0>();
      fence_regs(sac);
      pair_send(sac, sb, warp, lane, peer, 0, 4, T_OFF, B_SFULL, 2048);
      uint32_t g[16];
      const uint32_t bA = half2x(b2A), bB = half2x(b2B);
#pragma unroll
      for (int e = 0; e < 16; e++) {
        const uint32_t t = hfma2(pack2(acc[2 * e], acc[2 * e + 1]), 0x3f003f00u, (e & 1) ? bB : bA);
        const float ha = lo_f(t), hb = hi_f(t);
        g[e] = pack2(fmaf(ha, tanh_(ha), ha), fmaf(hb, tanh_(hb), hb));
      }
      mbar_wait(bars + B_FULL + 8 * rg.st, rg.ph);
      const uint32_t tile = sb + rg.st * SLOT + trow * 128;
      uint32_t xf[4][4];
#pragma unroll
      for (int j = 0; j < 4; j++) ldsm4(tile + swz + (((2 * j) ^ sx) << 4), xf[j]);
      pair_recv(sac, sb, warp, lane, 0, T_OFF, B_SFULL);
#pragma unroll
      for (int j = 0; j < 4; j++) {
#pragma unroll
        for (int i = 0; i < 4; i++) xf[j][i] = hadd2(xf[j][i], hmul2(pack2(sac[8 * j + 2 * i], sac[8 * j + 2 * i + 1]), g[4 * j + i]));
        stsm4(tile + swz + (((2 * j) ^ sx) << 4), xf[j][0], xf[j][1], xf[j][2], xf[j][3]);
      }
      __syncwarp();
      tile_to_global(tile, p.out + (size_t)(ti * 128 + trow) * D_ + own, D_, lane);
    }
  }
}

typedef CUresult (*EncodeFn)(CUtensorMap*, CUtensorMapDataType, cuuint32_t, void*, const cuuint64_t*, const cuuint64_t*, const cuuint32_t*,
                             const cuuint32_t*, CUtensorMapInterleave, CUtensorMapSwizzle, CUtensorMapL2promotion, CUtensorMapFloatOOBfill);

void make_map(EncodeFn enc, CUtensorMap* m, const void* ptr, uint64_t cols, uint64_t rows, uint32_t box_rows) {
  cuuint64_t gd[2] = {cols, rows};
  cuuint64_t gs[1] = {cols * 2};
  cuuint32_t bd[2] = {64, box_rows};
  cuuint32_t es[2] = {1, 1};
  CUresult r = enc(m, CU_TENSOR_MAP_DATA_TYPE_BFLOAT16, 2, const_cast<void*>(ptr), gd, gs, bd, es, CU_TENSOR_MAP_INTERLEAVE_NONE,
                   CU_TENSOR_MAP_SWIZZLE_128B, CU_TENSOR_MAP_L2_PROMOTION_L2_128B, CU_TENSOR_MAP_FLOAT_OOB_FILL_NONE);
  if (r != CUDA_SUCCESS) fprintf(stderr, "cuTensorMapEncodeTiled failed: %d\n", (int)r);
}

}

extern "C" void kernel_launch(void* const* d_in, const int* in_sizes, int n_in, void* d_out, int out_size) {
  (void)in_sizes; (void)n_in; (void)out_size;
  const bf16* x = (const bf16*)d_in[0];
  const bf16* wqkv = (const bf16*)d_in[1];
  const bf16* wo = (const bf16*)d_in[2];
  const bf16* w1 = (const bf16*)d_in[4];
  const bf16* b1 = (const bf16*)d_in[5];
  const bf16* w2 = (const bf16*)d_in[6];
  const bf16* b2 = (const bf16*)d_in[7];
  EncodeFn enc = nullptr;
  cudaDriverEntryPointQueryResult qr;
  cudaGetDriverEntryPoint("cuTensorMapEncodeTiled", (void**)&enc, cudaEnableDefault, &qr);
  void *h, *u, *o;
  cudaGetSymbolAddress(&h, g_h);
  cudaGetSymbolAddress(&u, g_u);
  cudaGetSymbolAddress(&o, g_o);
  Maps m;
  make_map(enc, &m.x2, x, 2 * D_, S_ / 2, 64);
  make_map(enc, &m.wq, wqkv, 3 * D_, D_, 64);
  make_map(enc, &m.w1, w1, F_, S_, 64);
  make_map(enc, &m.h, h, D_, S_, 64);
  make_map(enc, &m.o, o, D_, S_, 128);
  make_map(enc, &m.wo, wo, D_, D_, 64);
  make_map(enc, &m.w2, w2, S_, F_, 64);
  make_map(enc, &m.u, u, D_, F_, 64);
  make_map(enc, &m.xr, x, D_, S_, 128);
  Ptrs p{x, b1, b2, w1, w2, wo, wqkv, (bf16*)d_out, 0u};
  cudaFuncSetAttribute(fused_kernel, cudaFuncAttributeMaxDynamicSharedMemorySize, SMEM_BYTES);
  fused_kernel<<<128, 384, SMEM_BYTES>>>(p, m);
}
```
